```python
import torch

def _softmax(x, axis=-1):
    return torch.softmax(x, dim=axis)
def _gelu(x):
    return torch.nn.functional.gelu(x, approximate="tanh")
def _silu(x):
    return torch.nn.functional.silu(x)
def _sigmoid(x):
    return torch.sigmoid(x)
def _layernorm(x, axis=-1, eps=1e-5):
    m = x.mean(dim=axis, keepdim=True)
    v = x.var(dim=axis, keepdim=True, unbiased=False)
    return (x - m) / torch.sqrt(v + eps)
def _scatter_add(tgt, idx, src, axis=0):
    return tgt.clone().index_add_(axis, idx, src)
def _segment_sum(src, seg, n):
    out = torch.zeros((n,) + src.shape[1:], dtype=src.dtype)
    return out.index_add_(0, seg, src)
def _pad(x, pw):
    flat = tuple(v for pair in reversed(pw) for v in pair)
    return torch.nn.functional.pad(x, flat)

kernel_name = 'parallel_sum__grouped_kv_mqa__dense_activation_relu__prompt'

def setup_inputs():

    _w = (lambda a: (lambda t: t.to(torch.bfloat16) if t.is_floating_point() else t)(torch.as_tensor(a)))
    def _A_setup():
        B, S, D, H = 1, 2048, 512, 32
        Dh = D // H
        return {
            "x": _w((lambda *s: torch.randn(*s, dtype=torch.bfloat16) * 0.05)(B, S, D)),
            "wq": _w((lambda *s: torch.randn(*s, dtype=torch.bfloat16) * 0.2)(D, H * Dh)),
            "wk": _w((lambda *s: torch.randn(*s, dtype=torch.bfloat16) * 0.2)(D, Dh)),
            "wv": _w((lambda *s: torch.randn(*s, dtype=torch.bfloat16) * 0.1)(D, Dh)),
            "wo": _w((lambda *s: torch.randn(*s, dtype=torch.bfloat16) * 0.1)(H * Dh, D)),
        }
    _A_in = _A_setup()

    def _B_setup():
        B, S, D, Dff = 1, 2048, 512, 1792
        return {
            "x": _w((lambda *s: torch.randn(*s, dtype=torch.bfloat16) * 0.05)(B, S, D)),
            "w1": _w((lambda *s: torch.randn(*s, dtype=torch.bfloat16) * 0.1)(D, Dff)),
            "w2": _w((lambda *s: torch.randn(*s, dtype=torch.bfloat16) * 0.1)(Dff, D)),
        }
    _B_in = _B_setup()

    return {
        "A_x": _A_in["x"],
        "A_wq": _A_in["wq"],
        "A_wk": _A_in["wk"],
        "A_wv": _A_in["wv"],
        "A_wo": _A_in["wo"],
        "B_x": _B_in["x"],
        "B_w1": _B_in["w1"],
        "B_w2": _B_in["w2"],
    }

def reference(A_x, A_wq, A_wk, A_wv, A_wo, B_x, B_w1, B_w2):
    def _A_ref(x, wq, wk, wv, wo):
        B, S, D = x.shape
        H = 32
        Dh = D // H
        q = (lambda x, *d: x.permute(*d))((x @ wq).reshape(B, S, H, Dh), 0, 2, 1, 3)
        k = x @ wk
        v = x @ wv
        scores = torch.einsum("bhqd,bkd->bhqk", q, k) * (Dh ** -0.5)
        p = _softmax(scores, axis=-1)
        o = torch.einsum("bhqk,bkd->bhqd", p, v)
        return (lambda x, *d: x.permute(*d))(o, 0, 2, 1, 3).reshape(B, S, H * Dh) @ wo

    def _B_ref(x, w1, w2):
        h = torch.einsum("bsd,df->bsf", x, w1)
        zero = torch.zeros_like(h)
        h = torch.maximum(h, zero)
        return torch.einsum("bsf,fd->bsd", h, w2)

    x = A_x
    xn = _layernorm(x, axis=-1)
    return x + _A_ref(xn, A_wq, A_wk, A_wv, A_wo) + _B_ref(xn, B_w1, B_w2)
```

```cpp
#include <cuda_runtime.h>
#include <cuda.h>
#include <cuda_bf16.h>
#include <cuda_fp16.h>
#include <stdint.h>
#include <utility>

namespace {

constexpr int SEQ = 2048, DM = 512, DFF = 1792;
#define POLY_N 4
#define POLY_D 8
#define POLY_PAT 0
#define RDEC 112
#define RINC 176
#define PVCH 1

constexpr int UNIT = 8192;
__device__ __align__(1024) uint8_t g_kv[131072];
__device__ __align__(1024) uint8_t g_stat[1024];
__device__ __align__(1024) uint4   g_kvb[SEQ * 4];
__device__ __align__(1024) uint8_t g_xn[16 * 16 * UNIT];
__device__ __align__(1024) uint8_t g_h[16 * 56 * UNIT];
__device__ __align__(1024) uint8_t g_o[16 * 16 * UNIT];
__device__ __align__(1024) uint32_t g_sync[32 * (2 + 16 + 64)];
constexpr int SY_EPOCH = 0, SY_KV = 32, SY_H = 64, SY_O = 64 + 16 * 32;
#define TS(i) do {} while (0)
#define TSG(i) do {} while (0)

constexpr uint32_t OFF_XN = 0;
constexpr uint32_t OFF_K = 0, OFF_V = 65536;
constexpr uint32_t OFF_ONES = 131072;
constexpr uint32_t OFF_RING = 132096;
constexpr uint32_t OFF_WQ = OFF_RING, OFF_WK = OFF_RING + 65536, OFF_WV = OFF_RING + 81920;
constexpr uint32_t OFF_STAT = OFF_RING + 98304;
constexpr uint32_t OFF_BAR = OFF_STAT + 1024;
constexpr uint32_t SMEM_BYTES = OFF_BAR + 256;
constexpr uint32_t BAR_WQ = 0, BAR_WKV = 8, BAR_KV = 16, BAR_R1 = 80, BAR_R2 = 104;

template <class F, int... I> __device__ __forceinline__ void static_for_impl(F&& f, std::integer_sequence<int, I...>) { (f(std::integral_constant<int, I>{}), ...); }
template <int N, class F> __device__ __forceinline__ void static_for(F&& f) { static_for_impl(f, std::make_integer_sequence<int, N>{}); }

__device__ __forceinline__ void wg_fence() { asm volatile("wgmma.fence.sync.aligned;" ::: "memory"); }
__device__ __forceinline__ void wg_commit() { asm volatile("wgmma.commit_group.sync.aligned;" ::: "memory"); }
template <int N> __device__ __forceinline__ void wg_wait() { asm volatile("wgmma.wait_group.sync.aligned %0;" ::"n"(N) : "memory"); }
__device__ __forceinline__ void pin(float& x) { asm volatile("" : "+f"(x)::"memory"); }
__device__ __forceinline__ void pin(uint32_t& x) { asm volatile("" : "+r"(x)::"memory"); }
template <class T, int N> __device__ __forceinline__ void pin(T (&d)[N]) {
#pragma unroll
    for (int i = 0; i < N; i++) pin(d[i]);
}
__device__ __forceinline__ uint64_t mkdesc(uint32_t addr, uint32_t lbo, uint32_t sbo, uint32_t sw) {
    return (uint64_t)((addr >> 4) | ((lbo >> 4) << 16)) | ((uint64_t)((sbo >> 4) | (sw << 30)) << 32);
}
__device__ __forceinline__ void mbar_init(uint32_t bar, int cnt) { asm volatile("mbarrier.init.shared::cta.b64 [%0], %1;" ::"r"(bar), "r"(cnt) : "memory"); }
__device__ __forceinline__ void mbar_expect(uint32_t bar, uint32_t bytes) { asm volatile("mbarrier.arrive.expect_tx.shared::cta.b64 _, [%0], %1;" ::"r"(bar), "r"(bytes) : "memory"); }
__device__ __forceinline__ bool mbar_try(uint32_t bar, uint32_t par) {
    uint32_t r;
    asm volatile("{.reg .pred p; mbarrier.try_wait.parity.shared::cta.b64 p, [%1], %2; selp.u32 %0, 1, 0, p;}" : "=r"(r) : "r"(bar), "r"(par) : "memory");
    return r;
}
__device__ __forceinline__ void mbar_wait(uint32_t bar, uint32_t par) {
    int n = 0;
    while (!__all_sync(0xffffffffu, mbar_try(bar, par))) if (++n > (1 << 22)) asm volatile("trap;");
}
__device__ __forceinline__ bool elect() {
    uint32_t r;
    asm volatile("{.reg .pred p; elect.sync _|p, 0xffffffff; selp.u32 %0, 1, 0, p;}" : "=r"(r));
    return r;
}
__device__ __forceinline__ void bulk_g2s(uint32_t dst, const void* src, uint32_t bytes, uint32_t bar) {
    asm volatile("cp.async.bulk.shared::cluster.global.mbarrier::complete_tx::bytes [%0], [%1], %2, [%3];" ::"r"(dst), "l"(src), "r"(bytes), "r"(bar) : "memory");
}
__device__ __forceinline__ void bulk_s2g(void* dst, uint32_t src, uint32_t bytes) {
    asm volatile("cp.async.bulk.global.shared::cta.bulk_group [%0], [%1], %2;" ::"l"(dst), "r"(src), "r"(bytes) : "memory");
}
__device__ __forceinline__ void bulk_commit() { asm volatile("cp.async.bulk.commit_group;" ::: "memory"); }
__device__ __forceinline__ void bulk_wait_all() { asm volatile("cp.async.bulk.wait_group 0;" ::: "memory"); }
__device__ __forceinline__ void bulk_wait_read() { asm volatile("cp.async.bulk.wait_group.read 0;" ::: "memory"); }
__device__ __forceinline__ void l2_prefetch(const void* p, uint32_t bytes) { asm volatile("cp.async.bulk.prefetch.L2.global [%0], %1;" ::"l"(p), "r"(bytes) : "memory"); }
__device__ __forceinline__ void tma2(uint32_t dst, const CUtensorMap* m, uint32_t bar, int c0, int c1) {
    asm volatile("cp.async.bulk.tensor.2d.shared::cluster.global.mbarrier::complete_tx::bytes [%0], [%1, {%3, %4}], [%2];" ::"r"(dst), "l"(m), "r"(bar), "r"(c0), "r"(c1) : "memory");
}
__device__ __forceinline__ void tma3(uint32_t dst, const CUtensorMap* m, uint32_t bar, int c0, int c1, int c2) {
    asm volatile("cp.async.bulk.tensor.3d.shared::cluster.global.mbarrier::complete_tx::bytes [%0], [%1, {%3, %4, %5}], [%2];" ::"r"(dst), "l"(m), "r"(bar), "r"(c0), "r"(c1), "r"(c2) : "memory");
}
__device__ __forceinline__ void tma4(uint32_t dst, const CUtensorMap* m, uint32_t bar, int c0, int c1, int c2, int c3) {
    asm volatile("cp.async.bulk.tensor.4d.shared::cluster.global.mbarrier::complete_tx::bytes [%0], [%1, {%3, %4, %5, %6}], [%2];" ::"r"(dst), "l"(m), "r"(bar), "r"(c0), "r"(c1), "r"(c2), "r"(c3) : "memory");
}
__device__ __forceinline__ void tma2_store(const CUtensorMap* m, uint32_t src, int c0, int c1) {
    asm volatile("cp.async.bulk.tensor.2d.global.shared::cta.bulk_group [%0, {%2, %3}], [%1];" ::"l"(m), "r"(src), "r"(c0), "r"(c1) : "memory");
}
__device__ __forceinline__ void prefetch_map(const CUtensorMap* m) { asm volatile("prefetch.tensormap [%0];" ::"l"(m) : "memory"); }
__device__ __forceinline__ void fence_async_smem() { asm volatile("fence.proxy.async.shared::cta;" ::: "memory"); }
__device__ __forceinline__ void fence_async_all() { asm volatile("fence.proxy.async;" ::: "memory"); }
__device__ __forceinline__ void bar_sync(int id, int n) { asm volatile("bar.sync %0, %1;" ::"r"(id), "r"(n) : "memory"); }
__device__ __forceinline__ void bar_arrive(int id, int n) { asm volatile("bar.arrive %0, %1;" ::"r"(id), "r"(n) : "memory"); }
__device__ __forceinline__ bool bar_or(int id, int n, bool p) {
    uint32_t r;
    asm volatile("{.reg .pred a, b; setp.ne.u32 a, %3, 0; bar.red.or.pred b, %1, %2, a; selp.u32 %0, 1, 0, b;}" : "=r"(r) : "r"(id), "r"(n), "r"((uint32_t)p) : "memory");
    return r;
}
__device__ __forceinline__ void signal_add(uint32_t* p) {
    asm volatile("fence.acq_rel.gpu;" ::: "memory");
    asm volatile("red.relaxed.gpu.global.add.u32 [%0], 1;" ::"l"(p) : "memory");
}
__device__ __forceinline__ bool flag_ready(const uint32_t* p, uint32_t target) {
    uint32_t v;
    asm volatile("ld.acquire.gpu.global.u32 %0, [%1];" : "=r"(v) : "l"(p) : "memory");
    return __all_sync(0xffffffffu, (int)(v - target) >= 0);
}
__device__ __forceinline__ void flag_wait(const uint32_t* p, uint32_t target) {
    int n = 0;
    while (!flag_ready(p, target)) {
        if (++n > (1 << 22)) asm volatile("trap;");
    }
}
__device__ __forceinline__ void stsm4(uint32_t addr, uint32_t r0, uint32_t r1, uint32_t r2, uint32_t r3) {
    asm volatile("stmatrix.sync.aligned.m8n8.x4.shared.b16 [%0], {%1, %2, %3, %4};" ::"r"(addr), "r"(r0), "r"(r1), "r"(r2), "r"(r3) : "memory");
}
__device__ __forceinline__ uint32_t pack_bf16(float lo, float hi) { uint32_t d; asm("cvt.rn.bf16x2.f32 %0, %1, %2;" : "=r"(d) : "f"(hi), "f"(lo)); return d; }
__device__ __forceinline__ uint32_t pack_bf16_relu(float lo, float hi) { uint32_t d; asm("cvt.rn.relu.bf16x2.f32 %0, %1, %2;" : "=r"(d) : "f"(hi), "f"(lo)); return d; }
__device__ __forceinline__ uint32_t pack_f16(float lo, float hi) { uint32_t d; asm("cvt.rn.f16x2.f32 %0, %1, %2;" : "=r"(d) : "f"(hi), "f"(lo)); return d; }
__device__ __forceinline__ float bf_lo(uint32_t v) { return __uint_as_float(v << 16); }
__device__ __forceinline__ float bf_hi(uint32_t v) { return __uint_as_float(v & 0xffff0000u); }
__device__ __forceinline__ float bf_round(float x) { return bf_lo(pack_bf16(x, 0.f)); }
__device__ __forceinline__ uint32_t bf2fma(uint32_t a, uint32_t b, uint32_t c) { uint32_t d; asm("fma.rn.bf16x2 %0, %1, %2, %3;" : "=r"(d) : "r"(a), "r"(b), "r"(c)); return d; }
__device__ __forceinline__ uint32_t h2fma(uint32_t a, uint32_t b, uint32_t c) { uint32_t d; asm("fma.rn.f16x2 %0, %1, %2, %3;" : "=r"(d) : "r"(a), "r"(b), "r"(c)); return d; }
__device__ __forceinline__ uint32_t h2fma_sat(uint32_t a, uint32_t b, uint32_t c) { uint32_t d; asm("fma.rn.sat.f16x2 %0, %1, %2, %3;" : "=r"(d) : "r"(a), "r"(b), "r"(c)); return d; }
__device__ __forceinline__ uint32_t h2sub(uint32_t a, uint32_t b) { uint32_t d; asm("sub.f16x2 %0, %1, %2;" : "=r"(d) : "r"(a), "r"(b)); return d; }
__device__ __forceinline__ uint32_t h2mul(uint32_t a, uint32_t b) { uint32_t d; asm("mul.f16x2 %0, %1, %2;" : "=r"(d) : "r"(a), "r"(b)); return d; }
__device__ __forceinline__ uint32_t h2max(uint32_t a, uint32_t b) { uint32_t d; asm("max.f16x2 %0, %1, %2;" : "=r"(d) : "r"(a), "r"(b)); return d; }
__device__ __forceinline__ uint32_t h2ex2(uint32_t a) { uint32_t d; asm("ex2.approx.f16x2 %0, %1;" : "=r"(d) : "r"(a)); return d; }
__device__ __forceinline__ uint32_t prmt(uint32_t a, uint32_t b, uint32_t s) { uint32_t d; asm("prmt.b32 %0, %1, %2, %3;" : "=r"(d) : "r"(a), "r"(b), "r"(s)); return d; }
__device__ __forceinline__ float ex2f(float a) { float d; asm("ex2.approx.ftz.f32 %0, %1;" : "=f"(d) : "f"(a)); return d; }
__device__ __forceinline__ float h_lo(uint32_t a) { float d; asm("{.reg .b16 l, h; mov.b32 {l, h}, %1; cvt.f32.f16 %0, l;}" : "=f"(d) : "r"(a)); return d; }
__device__ __forceinline__ float h_hi(uint32_t a) { float d; asm("{.reg .b16 l, h; mov.b32 {l, h}, %1; cvt.f32.f16 %0, h;}" : "=f"(d) : "r"(a)); return d; }
__device__ __forceinline__ uint32_t bc_lo(uint32_t a) { uint32_t d; asm("{.reg .b16 l, h; mov.b32 {l, h}, %1; mov.b32 %0, {l, l};}" : "=r"(d) : "r"(a)); return d; }
__device__ __forceinline__ uint32_t bc_hi(uint32_t a) { uint32_t d; asm("{.reg .b16 l, h; mov.b32 {l, h}, %1; mov.b32 %0, {h, h};}" : "=r"(d) : "r"(a)); return d; }
__device__ __forceinline__ uint32_t ldg_here(const void* p) { uint32_t v; asm volatile("ld.global.nc.u32 %0, [%1];" : "=r"(v) : "l"(p) : "memory"); return v; }
__device__ __forceinline__ int imax_xor(int v, int m) { return max(v, __shfl_xor_sync(0xffffffffu, v, m)); }

__device__ __forceinline__ void wgmma_qk(uint32_t (&d)[64], const uint32_t (&a)[4], uint64_t bdesc) {
    asm volatile("wgmma.mma_async.sync.aligned.m64n256k16.f16.f16.f16 {"
        "%0, %1, %2, %3, %4, %5, %6, %7, %8, %9, %10, %11, %12, %13, %14, %15, "
        "%16, %17, %18, %19, %20, %21, %22, %23, %24, %25, %26, %27, %28, %29, %30, %31, "
        "%32, %33, %34, %35, %36, %37, %38, %39, %40, %41, %42, %43, %44, %45, %46, %47, "
        "%48, %49, %50, %51, %52, %53, %54, %55, %56, %57, %58, %59, %60, %61, %62, %63"
        "}, {%64, %65, %66, %67}, %68, 0, 1, 1, 0;\n"
        : "=r"(d[0]), "=r"(d[1]), "=r"(d[2]), "=r"(d[3]), "=r"(d[4]), "=r"(d[5]), "=r"(d[6]), "=r"(d[7]),
          "=r"(d[8]), "=r"(d[9]), "=r"(d[10]), "=r"(d[11]), "=r"(d[12]), "=r"(d[13]), "=r"(d[14]), "=r"(d[15]),
          "=r"(d[16]), "=r"(d[17]), "=r"(d[18]), "=r"(d[19]), "=r"(d[20]), "=r"(d[21]), "=r"(d[22]), "=r"(d[23]),
          "=r"(d[24]), "=r"(d[25]), "=r"(d[26]), "=r"(d[27]), "=r"(d[28]), "=r"(d[29]), "=r"(d[30]), "=r"(d[31]),
          "=r"(d[32]), "=r"(d[33]), "=r"(d[34]), "=r"(d[35]), "=r"(d[36]), "=r"(d[37]), "=r"(d[38]), "=r"(d[39]),
          "=r"(d[40]), "=r"(d[41]), "=r"(d[42]), "=r"(d[43]), "=r"(d[44]), "=r"(d[45]), "=r"(d[46]), "=r"(d[47]),
          "=r"(d[48]), "=r"(d[49]), "=r"(d[50]), "=r"(d[51]), "=r"(d[52]), "=r"(d[53]), "=r"(d[54]), "=r"(d[55]),
          "=r"(d[56]), "=r"(d[57]), "=r"(d[58]), "=r"(d[59]), "=r"(d[60]), "=r"(d[61]), "=r"(d[62]), "=r"(d[63])
        : "r"(a[0]), "r"(a[1]), "r"(a[2]), "r"(a[3]), "l"(bdesc));
}
__device__ __forceinline__ void wgmma_pv(float (&d)[12], uint32_t a0, uint32_t a1, uint32_t a2, uint32_t a3, uint64_t bdesc) {
    asm volatile("wgmma.mma_async.sync.aligned.m64n24k16.f32.f16.f16 {"
        "%0, %1, %2, %3, %4, %5, %6, %7, %8, %9, %10, %11"
        "}, {%12, %13, %14, %15}, %16, 1, 1, 1, 1;\n"
        : "+f"(d[0]), "+f"(d[1]), "+f"(d[2]), "+f"(d[3]), "+f"(d[4]), "+f"(d[5]), "+f"(d[6]), "+f"(d[7]),
          "+f"(d[8]), "+f"(d[9]), "+f"(d[10]), "+f"(d[11])
        : "r"(a0), "r"(a1), "r"(a2), "r"(a3), "l"(bdesc));
}
__device__ __forceinline__ void wgmma_ss(float (&d)[8], uint64_t adesc, uint64_t bdesc) {
    asm volatile("wgmma.mma_async.sync.aligned.m64n16k16.f32.bf16.bf16 {"
        "%0, %1, %2, %3, %4, %5, %6, %7"
        "}, %8, %9, 1, 1, 1, 0, 1;\n"
        : "+f"(d[0]), "+f"(d[1]), "+f"(d[2]), "+f"(d[3]), "+f"(d[4]), "+f"(d[5]), "+f"(d[6]), "+f"(d[7])
        : "l"(adesc), "l"(bdesc));
}
__device__ __forceinline__ void wgmma_ss(float (&d)[16], uint64_t adesc, uint64_t bdesc) {
    asm volatile("wgmma.mma_async.sync.aligned.m64n32k16.f32.bf16.bf16 {"
        "%0, %1, %2, %3, %4, %5, %6, %7, %8, %9, %10, %11, %12, %13, %14, %15"
        "}, %16, %17, 1, 1, 1, 0, 1;\n"
        : "+f"(d[0]), "+f"(d[1]), "+f"(d[2]), "+f"(d[3]), "+f"(d[4]), "+f"(d[5]), "+f"(d[6]), "+f"(d[7]),
          "+f"(d[8]), "+f"(d[9]), "+f"(d[10]), "+f"(d[11]), "+f"(d[12]), "+f"(d[13]), "+f"(d[14]), "+f"(d[15])
        : "l"(adesc), "l"(bdesc));
}
__device__ __forceinline__ void wgmma_ss(float (&d)[24], uint64_t adesc, uint64_t bdesc) {
    asm volatile("wgmma.mma_async.sync.aligned.m64n48k16.f32.bf16.bf16 {"
        "%0, %1, %2, %3, %4, %5, %6, %7, %8, %9, %10, %11, %12, %13, %14, %15, "
        "%16, %17, %18, %19, %20, %21, %22, %23"
        "}, %24, %25, 1, 1, 1, 0, 1;\n"
        : "+f"(d[0]), "+f"(d[1]), "+f"(d[2]), "+f"(d[3]), "+f"(d[4]), "+f"(d[5]), "+f"(d[6]), "+f"(d[7]),
          "+f"(d[8]), "+f"(d[9]), "+f"(d[10]), "+f"(d[11]), "+f"(d[12]), "+f"(d[13]), "+f"(d[14]), "+f"(d[15]),
          "+f"(d[16]), "+f"(d[17]), "+f"(d[18]), "+f"(d[19]), "+f"(d[20]), "+f"(d[21]), "+f"(d[22]), "+f"(d[23])
        : "l"(adesc), "l"(bdesc));
}
__device__ __forceinline__ void wgmma_ss(float (&d)[32], uint64_t adesc, uint64_t bdesc) {
    asm volatile("wgmma.mma_async.sync.aligned.m64n64k16.f32.bf16.bf16 {"
        "%0, %1, %2, %3, %4, %5, %6, %7, %8, %9, %10, %11, %12, %13, %14, %15, "
        "%16, %17, %18, %19, %20, %21, %22, %23, %24, %25, %26, %27, %28, %29, %30, %31"
        "}, %32, %33, 1, 1, 1, 0, 1;\n"
        : "+f"(d[0]), "+f"(d[1]), "+f"(d[2]), "+f"(d[3]), "+f"(d[4]), "+f"(d[5]), "+f"(d[6]), "+f"(d[7]),
          "+f"(d[8]), "+f"(d[9]), "+f"(d[10]), "+f"(d[11]), "+f"(d[12]), "+f"(d[13]), "+f"(d[14]), "+f"(d[15]),
          "+f"(d[16]), "+f"(d[17]), "+f"(d[18]), "+f"(d[19]), "+f"(d[20]), "+f"(d[21]), "+f"(d[22]), "+f"(d[23]),
          "+f"(d[24]), "+f"(d[25]), "+f"(d[26]), "+f"(d[27]), "+f"(d[28]), "+f"(d[29]), "+f"(d[30]), "+f"(d[31])
        : "l"(adesc), "l"(bdesc));
}
__device__ __forceinline__ void wgmma_ss(float (&d)[48], uint64_t adesc, uint64_t bdesc) {
    asm volatile("wgmma.mma_async.sync.aligned.m64n96k16.f32.bf16.bf16 {"
        "%0, %1, %2, %3, %4, %5, %6, %7, %8, %9, %10, %11, %12, %13, %14, %15, "
        "%16, %17, %18, %19, %20, %21, %22, %23, %24, %25, %26, %27, %28, %29, %30, %31, "
        "%32, %33, %34, %35, %36, %37, %38, %39, %40, %41, %42, %43, %44, %45, %46, %47"
        "}, %48, %49, 1, 1, 1, 0, 1;\n"
        : "+f"(d[0]), "+f"(d[1]), "+f"(d[2]), "+f"(d[3]), "+f"(d[4]), "+f"(d[5]), "+f"(d[6]), "+f"(d[7]),
          "+f"(d[8]), "+f"(d[9]), "+f"(d[10]), "+f"(d[11]), "+f"(d[12]), "+f"(d[13]), "+f"(d[14]), "+f"(d[15]),
          "+f"(d[16]), "+f"(d[17]), "+f"(d[18]), "+f"(d[19]), "+f"(d[20]), "+f"(d[21]), "+f"(d[22]), "+f"(d[23]),
          "+f"(d[24]), "+f"(d[25]), "+f"(d[26]), "+f"(d[27]), "+f"(d[28]), "+f"(d[29]), "+f"(d[30]), "+f"(d[31]),
          "+f"(d[32]), "+f"(d[33]), "+f"(d[34]), "+f"(d[35]), "+f"(d[36]), "+f"(d[37]), "+f"(d[38]), "+f"(d[39]),
          "+f"(d[40]), "+f"(d[41]), "+f"(d[42]), "+f"(d[43]), "+f"(d[44]), "+f"(d[45]), "+f"(d[46]), "+f"(d[47])
        : "l"(adesc), "l"(bdesc));
}
__device__ __forceinline__ void wgmma_ss(float (&d)[64], uint64_t adesc, uint64_t bdesc) {
    asm volatile("wgmma.mma_async.sync.aligned.m64n128k16.f32.bf16.bf16 {"
        "%0, %1, %2, %3, %4, %5, %6, %7, %8, %9, %10, %11, %12, %13, %14, %15, "
        "%16, %17, %18, %19, %20, %21, %22, %23, %24, %25, %26, %27, %28, %29, %30, %31, "
        "%32, %33, %34, %35, %36, %37, %38, %39, %40, %41, %42, %43, %44, %45, %46, %47, "
        "%48, %49, %50, %51, %52, %53, %54, %55, %56, %57, %58, %59, %60, %61, %62, %63"
        "}, %64, %65, 1, 1, 1, 0, 1;\n"
        : "+f"(d[0]), "+f"(d[1]), "+f"(d[2]), "+f"(d[3]), "+f"(d[4]), "+f"(d[5]), "+f"(d[6]), "+f"(d[7]),
          "+f"(d[8]), "+f"(d[9]), "+f"(d[10]), "+f"(d[11]), "+f"(d[12]), "+f"(d[13]), "+f"(d[14]), "+f"(d[15]),
          "+f"(d[16]), "+f"(d[17]), "+f"(d[18]), "+f"(d[19]), "+f"(d[20]), "+f"(d[21]), "+f"(d[22]), "+f"(d[23]),
          "+f"(d[24]), "+f"(d[25]), "+f"(d[26]), "+f"(d[27]), "+f"(d[28]), "+f"(d[29]), "+f"(d[30]), "+f"(d[31]),
          "+f"(d[32]), "+f"(d[33]), "+f"(d[34]), "+f"(d[35]), "+f"(d[36]), "+f"(d[37]), "+f"(d[38]), "+f"(d[39]),
          "+f"(d[40]), "+f"(d[41]), "+f"(d[42]), "+f"(d[43]), "+f"(d[44]), "+f"(d[45]), "+f"(d[46]), "+f"(d[47]),
          "+f"(d[48]), "+f"(d[49]), "+f"(d[50]), "+f"(d[51]), "+f"(d[52]), "+f"(d[53]), "+f"(d[54]), "+f"(d[55]),
          "+f"(d[56]), "+f"(d[57]), "+f"(d[58]), "+f"(d[59]), "+f"(d[60]), "+f"(d[61]), "+f"(d[62]), "+f"(d[63])
        : "l"(adesc), "l"(bdesc));
}

#define H2C(x) ((uint32_t)(x) * 0x00010001u)
constexpr uint32_t C_2M15 = H2C(0x0200), C_N2M15 = H2C(0x8200), C_2P15 = H2C(0x7800), C_N2P15 = H2C(0xF800);
constexpr uint32_t C_512 = H2C(0x6000), C_N512 = H2C(0xE000), C_OFF27 = H2C(27), C_N13P5 = H2C(0xCAC0);
constexpr uint32_t PC0 = H2C(0x05a8), PC1 = H2C(0x27d9), PC2 = H2C(0x4581), PC3 = H2C(0x60ea);
constexpr float Q_SCALE = 0.25f * 1.4426950408889634f;

__device__ __forceinline__ uint32_t exp_mufu(uint32_t s, uint32_t cx) { return h2ex2(h2fma(s, C_512, cx)); }
__device__ __forceinline__ uint32_t exp_fma(uint32_t s, uint32_t cr, uint32_t ct) {
    const uint32_t r = h2fma_sat(s, C_2M15, cr);
    const uint32_t t = h2fma(r, C_2P15, ct);
    const uint32_t f = h2sub(s, t);
    uint32_t p = h2fma(f, PC3, PC2);
    p = h2fma(p, f, PC1);
    p = h2fma_sat(p, f, PC0);
    return (r << 10) + p;
}
__host__ __device__ constexpr bool is_poly(int i) {
    return POLY_PAT == 0 ? (((i % POLY_D) + 1) * POLY_N / POLY_D != (i % POLY_D) * POLY_N / POLY_D)
         : POLY_PAT == 1 ? ((i % POLY_D) < POLY_N)
         : POLY_PAT == 2 ? ((i % POLY_D) >= POLY_D - POLY_N)
                         : ((((i % POLY_D) + 1) * POLY_N + POLY_D / 2) / POLY_D != ((i % POLY_D) * POLY_N + POLY_D / 2) / POLY_D);
}

constexpr long long K_INC = 512;
constexpr long long V_INC = 32 - (32 << 16);

__device__ __forceinline__ void attn_tile(float (&O)[12], const uint32_t (&q)[4], uint32_t& mrun, uint32_t& cxp, uint64_t kd, uint64_t vd) {
    uint32_t S[64];
    wg_fence();
    wgmma_qk(S, q, kd);
    wg_commit();
    wg_wait<0>();
    pin(S);
    uint32_t ma = h2max(S[0], S[2]), mb = h2max(S[1], S[3]), mc = h2max(S[4], S[6]), md = h2max(S[5], S[7]);
#pragma unroll
    for (int i = 8; i < 64; i += 8) {
        ma = h2max(h2max(ma, S[i]), S[i + 2]);
        mb = h2max(h2max(mb, S[i + 1]), S[i + 3]);
        mc = h2max(h2max(mc, S[i + 4]), S[i + 6]);
        md = h2max(h2max(md, S[i + 5]), S[i + 7]);
    }
    uint32_t m = h2max(h2max(prmt(ma, mb, 0x5410), prmt(ma, mb, 0x7632)), h2max(prmt(mc, md, 0x5410), prmt(mc, md, 0x7632)));
    m = h2max(m, __shfl_xor_sync(0xffffffffu, m, 1));
    m = h2max(h2max(m, mrun), __shfl_xor_sync(0xffffffffu, m, 2));
    mrun = m;
    const uint32_t cr = h2fma(m, C_N2M15, C_OFF27);
    const uint32_t ct = h2mul(cr, C_N2P15);
    const uint32_t cx = h2fma(ct, C_N512, C_N13P5);
    const uint32_t dd = h2sub(cx, cxp);
    cxp = cx;
    const float a0 = ex2f(h_lo(dd)), a1 = ex2f(h_hi(dd));
    const uint32_t crA = bc_lo(cr), crB = bc_hi(cr), ctA = bc_lo(ct), ctB = bc_hi(ct), cxA = bc_lo(cx), cxB = bc_hi(cx);
#pragma unroll
    for (int i = 0; i < 12; i++) O[i] *= (i & 2) ? a1 : a0;
    static_for<16 / PVCH>([&](auto c) {
        constexpr int C = decltype(c)::value;
#pragma unroll
        for (int i = 4 * PVCH * C; i < 4 * PVCH * (C + 1); i++) {
            if (is_poly(i)) S[i] = exp_fma(S[i], (i & 1) ? crB : crA, (i & 1) ? ctB : ctA);
            else            S[i] = exp_mufu(S[i], (i & 1) ? cxB : cxA);
        }
        wg_fence();
#pragma unroll
        for (int k = PVCH * C; k < PVCH * (C + 1); k++) wgmma_pv(O, S[4 * k], S[4 * k + 1], S[4 * k + 2], S[4 * k + 3], vd + k * V_INC);
    });
    wg_commit();
    wg_wait<0>();
    pin(O);
}

__device__ __forceinline__ void attn_slow(const uint32_t (&qb)[12], uint8_t* ounit, int r0, int chunk0, int lane) {
    const int row = lane >> 1, half = lane & 1;
    float qf[16];
#pragma unroll
    for (int d = 0; d < 16; d += 2) {
        const int src = 4 * (row & 7) + ((d & 7) >> 1);
        const uint32_t v0 = __shfl_sync(0xffffffffu, qb[(d >> 3) * 2], src), v1 = __shfl_sync(0xffffffffu, qb[(d >> 3) * 2 + 1], src);
        const uint32_t w = (row & 8) ? v1 : v0;
        qf[d] = bf_lo(w) * Q_SCALE;
        qf[d + 1] = bf_hi(w) * Q_SCALE;
    }
    float m = -INFINITY, l = 0.f, o[16];
#pragma unroll
    for (int d = 0; d < 16; d++) o[d] = 0.f;
#pragma unroll 1
    for (int j = half * 1024; j < half * 1024 + 1024; j++) {
        uint32_t kv[16];
#pragma unroll
        for (int i = 0; i < 4; i++) {
            const uint4 t = __ldcg(&g_kvb[j * 4 + i]);
            kv[4 * i] = t.x; kv[4 * i + 1] = t.y; kv[4 * i + 2] = t.z; kv[4 * i + 3] = t.w;
        }
        float s = 0.f;
#pragma unroll
        for (int i = 0; i < 8; i++) s = fmaf(qf[2 * i + 1], bf_hi(kv[i]), fmaf(qf[2 * i], bf_lo(kv[i]), s));
        const float mn = fmaxf(m, s), a = exp2f(m - mn), p = exp2f(s - mn);
        m = mn;
        l = fmaf(l, a, p);
#pragma unroll
        for (int i = 0; i < 8; i++) {
            o[2 * i] = fmaf(o[2 * i], a, p * bf_lo(kv[8 + i]));
            o[2 * i + 1] = fmaf(o[2 * i + 1], a, p * bf_hi(kv[8 + i]));
        }
    }
    const float m2 = __shfl_xor_sync(0xffffffffu, m, 1), mn = fmaxf(m, m2), a = exp2f(m - mn);
    l *= a;
    l += __shfl_xor_sync(0xffffffffu, l, 1);
    const float inv = 1.f / l;
    uint32_t w[8];
#pragma unroll
    for (int i = 0; i < 8; i++) {
        float e0 = o[2 * i] * a, e1 = o[2 * i + 1] * a;
        e0 += __shfl_xor_sync(0xffffffffu, e0, 1);
        e1 += __shfl_xor_sync(0xffffffffu, e1, 1);
        w[i] = pack_bf16(e0 * inv, e1 * inv);
    }
    const int R = r0 + row;
    const uint4 val = half ? make_uint4(w[4], w[5], w[6], w[7]) : make_uint4(w[0], w[1], w[2], w[3]);
    *(uint4*)(ounit + R * 64 + (((chunk0 + half) ^ ((R >> 1) & 3)) << 4)) = val;
}

template <int NR>
__device__ __forceinline__ void gemm_item(float (&c0)[NR], float (&c1)[NR], uint32_t a, uint32_t b) {
    const uint64_t ad = mkdesc(a, 16, 512, 2), bd = mkdesc(b, 4096, 512, 2);
    wg_fence();
#pragma unroll
    for (int k = 0; k < 4; k++) {
        wgmma_ss(c0, ad + (k >> 1) * 512 + (k & 1) * 2, bd + k * 64);
        wgmma_ss(c1, ad + 256 + (k >> 1) * 512 + (k & 1) * 2, bd + k * 64);
    }
    wg_commit();
}
template <int NU>
__device__ __forceinline__ void stage_h(const float (&c)[NU * 16], uint32_t dst, int row0, int lane) {
    const int row = row0 + ((lane >> 3) & 1) * 8 + (lane & 7), sw = (row >> 1) & 3;
#pragma unroll
    for (int j = 0; j < NU * 4; j += 2)
        stsm4(dst + (j >> 2) * UNIT + row * 64 + ((((j & 3) + (lane >> 4)) ^ sw) << 4),
              pack_bf16_relu(c[4 * j], c[4 * j + 1]), pack_bf16_relu(c[4 * j + 2], c[4 * j + 3]),
              pack_bf16_relu(c[4 * j + 4], c[4 * j + 5]), pack_bf16_relu(c[4 * j + 6], c[4 * j + 7]));
}

struct Params {
    CUtensorMap wq, wk, wv, w1a, w1b, w2, wo, out;
    const __nv_bfloat16* x;
    const uint8_t *w1p, *w2p, *wop;
};

__global__ void __launch_bounds__(512, 1) fused_mqa_ffn_kernel(const __grid_constant__ Params P) {
    extern __shared__ __align__(1024) uint8_t smem[];
    const uint32_t sb = (uint32_t)__cvta_generic_to_shared(smem);
    const int tid = threadIdx.x, lane = tid & 31, g = lane >> 2, t4 = lane & 3;
    const int warp = __shfl_sync(0xffffffffu, tid >> 5, 0), wg = warp >> 2, wq4 = warp & 3;
    const int rb = blockIdx.x >> 3, c = blockIdx.x & 7;
    const uint32_t bars = sb + OFF_BAR;
    if (tid == 0) { TS(0); TSG(60); }

    uint4 xv[16];
    {
        const uint4* xr = (const uint4*)(P.x + (size_t)(rb * 128 + warp * 8 + g) * DM) + t4;
#pragma unroll
        for (int i = 0; i < 16; i++) xv[i] = __ldg(xr + 4 * i);
    }
    uint32_t epoch = 0;
    if (warp == 12) {
      if (elect()) {
        if (sb & 1023) asm volatile("trap;");
        mbar_init(bars + BAR_WQ, 1);
        mbar_init(bars + BAR_WKV, 1);
        for (int i = 0; i < 8; i++) mbar_init(bars + BAR_KV + 8 * i, 1);
        for (int i = 0; i < 3; i++) mbar_init(bars + BAR_R1 + 8 * i, 1);
        for (int i = 0; i < 4; i++) mbar_init(bars + BAR_R2 + 8 * i, 1);
        fence_async_all();
        mbar_expect(bars + BAR_WKV, 32768);
        tma2(sb + OFF_WK, &P.wk, bars + BAR_WKV, 0, 0);
        tma2(sb + OFF_WK + 8192, &P.wk, bars + BAR_WKV, 0, 256);
        tma2(sb + OFF_WV, &P.wv, bars + BAR_WKV, 0, 0);
        tma2(sb + OFF_WV + 8192, &P.wv, bars + BAR_WKV, 0, 256);
        mbar_expect(bars + BAR_WQ, 65536);
        tma3(sb + OFF_WQ, &P.wq, bars + BAR_WQ, 0, 0, 4 * c);
        tma3(sb + OFF_WQ + 32768, &P.wq, bars + BAR_WQ, 0, 256, 4 * c);
        prefetch_map(&P.w1a); prefetch_map(&P.w1b); prefetch_map(&P.w2); prefetch_map(&P.wo); prefetch_map(&P.out);
      }
      asm volatile("ld.relaxed.gpu.global.u32 %0, [%1];" : "=r"(epoch) : "l"(&g_sync[SY_EPOCH]) : "memory");
    }
    if (tid < 128) *(uint32_t*)(smem + OFF_ONES + 4 * tid) = 0x3c003c00u;
    {
        float acc[4][4];
#pragma unroll
        for (int i = 0; i < 4; i++)
#pragma unroll
            for (int j = 0; j < 4; j++) acc[i][j] = 0.f;
#pragma unroll
        for (int i = 0; i < 32; i++) {
            const uint32_t w0 = (i & 1) ? xv[i >> 1].z : xv[i >> 1].x, w1 = (i & 1) ? xv[i >> 1].w : xv[i >> 1].y;
            asm volatile("mma.sync.aligned.m16n8k16.row.col.f32.bf16.bf16.f32 {%0, %1, %2, %3}, {%4, %6, %5, %6}, {%4, %5}, {%0, %1, %2, %3};"
                         : "+f"(acc[i & 3][0]), "+f"(acc[i & 3][1]), "+f"(acc[i & 3][2]), "+f"(acc[i & 3][3])
                         : "r"(w0), "r"(w1), "r"(0x3f803f80u));
        }
        const int e = g & 1;
        float ssq = e ? (acc[0][1] + acc[1][1]) + (acc[2][1] + acc[3][1]) : (acc[0][0] + acc[1][0]) + (acc[2][0] + acc[3][0]);
        float sum = e ? (acc[0][3] + acc[1][3]) + (acc[2][3] + acc[3][3]) : (acc[0][2] + acc[1][2]) + (acc[2][2] + acc[3][2]);
        ssq = __shfl_sync(0xffffffffu, ssq, 4 * g + (g >> 1));
        sum = __shfl_sync(0xffffffffu, sum, 4 * g + (g >> 1));
        if (tid == 0) TS(1);
        const float mean = sum * (1.f / DM);
        const float var = fmaxf(fmaf(-mean, mean, ssq * (1.f / DM)), 0.f);
        const float sd = bf_round(sqrtf(bf_round(bf_round(var) + 1e-5f)));
        const float r = 1.f / sd, rh = bf_round(r);
        const uint32_t rhi = pack_bf16(rh, rh), rlo = pack_bf16(r - rh, r - rh);
        const float cm = -bf_round(mean) * r;
        const uint32_t cc = pack_bf16(cm, cm);
        const int row = warp * 8 + g;
        const uint32_t dst = sb + OFF_XN + row * 64 + ((t4 ^ ((row >> 1) & 3)) << 4);
#pragma unroll
        for (int i = 0; i < 16; i++) {
            const uint32_t y0 = bf2fma(xv[i].x, rhi, bf2fma(xv[i].x, rlo, cc)), y1 = bf2fma(xv[i].y, rhi, bf2fma(xv[i].y, rlo, cc));
            const uint32_t y2 = bf2fma(xv[i].z, rhi, bf2fma(xv[i].z, rlo, cc)), y3 = bf2fma(xv[i].w, rhi, bf2fma(xv[i].w, rlo, cc));
            asm volatile("st.shared.v4.b32 [%0], {%1, %2, %3, %4};" ::"r"(dst + i * UNIT), "r"(y0), "r"(y1), "r"(y2), "r"(y3) : "memory");
        }
    }
    fence_async_smem();
    __syncthreads();
    if (tid == 0) TS(2);

    if (wg < 3) {
        asm volatile("setmaxnreg.dec.sync.aligned.u32 %0;" ::"n"(RDEC));
        uint32_t qb[12];
        mbar_wait(bars + BAR_WQ, 0);
        if (wg < 2) {
            float a[24];
#pragma unroll
            for (int i = 0; i < 24; i++) a[i] = 0.f;
            pin(a);
            const uint64_t ad = mkdesc(sb + OFF_XN + wg * 4096, 16, 512, 2), bd = mkdesc(sb + OFF_WQ, 8192, 256, 3);
            wg_fence();
#pragma unroll
            for (int k = 0; k < 32; k++) wgmma_ss(a, ad + (k >> 1) * 512 + (k & 1) * 2, bd + (k >> 4) * 2048 + (k & 15) * 32);
            wg_commit();
            wg_wait<0>();
            pin(a);
#pragma unroll
            for (int i = 0; i < 12; i++) qb[i] = pack_bf16(a[2 * i], a[2 * i + 1]);
        } else {
            float a[8], b[8];
#pragma unroll
            for (int i = 0; i < 8; i++) { a[i] = 0.f; b[i] = 0.f; }
            pin(a); pin(b);
            const uint64_t ad = mkdesc(sb + OFF_XN, 16, 512, 2), bd = mkdesc(sb + OFF_WQ + 3 * 8192, 8192, 256, 3);
            wg_fence();
#pragma unroll
            for (int k = 0; k < 32; k++) {
                wgmma_ss(a, ad + (k >> 1) * 512 + (k & 1) * 2, bd + (k >> 4) * 2048 + (k & 15) * 32);
                wgmma_ss(b, ad + 256 + (k >> 1) * 512 + (k & 1) * 2, bd + (k >> 4) * 2048 + (k & 15) * 32);
            }
            wg_commit();
            wg_wait<0>();
            pin(a); pin(b);
#pragma unroll
            for (int i = 0; i < 4; i++) { qb[i] = pack_bf16(a[2 * i], a[2 * i + 1]); qb[4 + i] = pack_bf16(b[2 * i], b[2 * i + 1]); qb[8 + i] = 0; }
        }
        bar_arrive(1, 512);
        if (tid == 0) TS(3);
        int q2 = 0;
#pragma unroll
        for (int i = 0; i < 6; i++) {
            const int j = (i >> 1) * 4 + (i & 1);
            float s = bf_lo(qb[j]) * bf_lo(qb[j]);
            s = fmaf(bf_hi(qb[j]), bf_hi(qb[j]), s);
            s = fmaf(bf_lo(qb[j + 2]), bf_lo(qb[j + 2]), s);
            s = fmaf(bf_hi(qb[j + 2]), bf_hi(qb[j + 2]), s);
            s += __shfl_xor_sync(0xffffffffu, s, 1);
            s += __shfl_xor_sync(0xffffffffu, s, 2);
            q2 = max(q2, __float_as_int(s) & 0x7fffffff);
        }
        mbar_wait(bars + BAR_KV, 0);
        bool slow;
        {
            const int4 s0 = *(const int4*)(smem + OFF_STAT + lane * 32), s1 = *(const int4*)(smem + OFF_STAT + lane * 32 + 16);
            int k2 = max(max(s0.x, s0.z), max(s1.x, s1.z)), vm = max(max(s0.y, s0.w), max(s1.y, s1.w));
#pragma unroll
            for (int m = 1; m < 32; m <<= 1) { k2 = imax_xor(k2, m); vm = imax_xor(vm, m); }
            const float qn2 = __int_as_float(q2) * (Q_SCALE * Q_SCALE), kn2 = __int_as_float(k2), vx = __int_as_float(vm);
            const bool ok = (qn2 * kn2 < 960.f * 960.f) && (qn2 < 1.6e7f) && (kn2 < 1.6e7f) && (vx < 6.0e4f) && (vx > 9.7e-4f);
            slow = bar_or(2 + wg, 128, !ok);
        }
        if (tid == 0) TS(4);
        const int nround = wg < 2 ? 3 : 2;
        const uint64_t kd0 = mkdesc(sb + OFF_K, 16, 256, 3), vd0 = mkdesc(sb + OFF_V, OFF_ONES - OFF_V, 256, 3);
#pragma unroll 1
        for (int r = 0; r < nround; r++) {
            const int h = wg < 2 ? r : 3, r0 = (wg < 2 ? wg : r) * 64 + wq4 * 16;
            uint8_t* ounit = g_o + (size_t)((rb * 4 + h) * 4 + (c >> 1)) * UNIT;
            if (!slow) {
                uint32_t q[4];
#pragma unroll
                for (int i = 0; i < 4; i++) q[i] = pack_f16(bf_lo(qb[i]) * (Q_SCALE / 32.f), bf_hi(qb[i]) * (Q_SCALE / 32.f));
                float O[12];
#pragma unroll
                for (int i = 0; i < 12; i++) O[i] = 0.f;
                pin(O);
                uint32_t mrun = H2C(0xFBFF), cxp = H2C(0x7C00);
                uint64_t kd = kd0, vd = vd0;
#pragma unroll 1
                for (int t = 0; t < 8; t++) {
                    if (r == 0) mbar_wait(bars + BAR_KV + 8 * t, 0);
                    attn_tile(O, q, mrun, cxp, kd, vd);
                    kd += K_INC;
                    vd += (uint64_t)(16 * V_INC);
                }
                const float i0 = 1.f / O[8], i1 = 1.f / O[10];
                const int R = r0 + g, sw = (R >> 1) & 3, ch = (c & 1) * 2;
                uint8_t* p = ounit + R * 64 + 4 * t4;
                *(uint32_t*)(p + ((ch ^ sw) << 4)) = pack_bf16(O[0] * i0, O[1] * i0);
                *(uint32_t*)(p + (((ch + 1) ^ sw) << 4)) = pack_bf16(O[4] * i0, O[5] * i0);
                *(uint32_t*)(p + 512 + ((ch ^ sw) << 4)) = pack_bf16(O[2] * i1, O[3] * i1);
                *(uint32_t*)(p + 512 + (((ch + 1) ^ sw) << 4)) = pack_bf16(O[6] * i1, O[7] * i1);
            } else {
                attn_slow(qb, ounit, r0, (c & 1) * 2, lane);
            }
            __syncwarp();
            if (lane == 0) signal_add(&g_sync[SY_O + (rb * 4 + h) * 32]);
            if (tid == 0) TS(5 + r);
            if (tid == 256) TS(8 + r);
#pragma unroll
            for (int i = 0; i < 8; i++) qb[i] = qb[i + 4];
        }
    } else {
        asm volatile("setmaxnreg.inc.sync.aligned.u32 %0;" ::"n"(RINC));
        const bool prod = warp == 12;
        const bool kvwarp = wq4 == (c & 3);
        if (kvwarp && lane < 16) {
            bulk_s2g(g_xn + (size_t)(rb * 16 + lane) * UNIT + c * 1024, sb + OFF_XN + lane * UNIT + c * 1024, 1024);
            bulk_commit();
        }
        {
            float a[16];
#pragma unroll
            for (int i = 0; i < 16; i++) a[i] = 0.f;
            pin(a);
            mbar_wait(bars + BAR_WKV, 0);
            const uint64_t ad = mkdesc(sb + OFF_XN + (c >> 2) * 4096, 16, 512, 2), bd = mkdesc(sb + OFF_WK, 16384, 256, 3);
            wg_fence();
#pragma unroll
            for (int k = 0; k < 32; k++) wgmma_ss(a, ad + (k >> 1) * 512 + (k & 1) * 2, bd + k * 32);
            wg_commit();
            wg_wait<0>();
            pin(a);
            if (kvwarp) {
                uint32_t w[8];
#pragma unroll
                for (int i = 0; i < 8; i++) w[i] = pack_bf16(a[2 * i], a[2 * i + 1]);
                int k2 = 0, vm = 0;
#pragma unroll
                for (int hh = 0; hh < 2; hh++) {
                    const int key = rb * 128 + c * 16 + g + 8 * hh, sw = (key >> 2) & 1;
                    uint8_t* pk = g_kv + key * 32 + 4 * t4;
                    uint32_t* pb = (uint32_t*)g_kvb + key * 16 + t4;
                    float s = 0.f;
#pragma unroll
                    for (int b = 0; b < 2; b++) {
                        const uint32_t kk = w[2 * b + hh], vv = w[4 + 2 * b + hh];
                        *(uint32_t*)(pk + ((b ^ sw) << 4)) = pack_f16(bf_lo(kk) * 0.0625f, bf_hi(kk) * 0.0625f);
                        *(uint32_t*)(pk + 65536 + ((b ^ sw) << 4)) = pack_f16(bf_lo(vv), bf_hi(vv));
                        pb[4 * b] = kk;
                        pb[8 + 4 * b] = vv;
                        s = fmaf(bf_lo(kk), bf_lo(kk), fmaf(bf_hi(kk), bf_hi(kk), s));
                        vm = max(vm, max((int)((vv << 16) & 0x7fffffff), (int)(vv & 0x7fff0000)));
                    }
                    s += __shfl_xor_sync(0xffffffffu, s, 1);
                    s += __shfl_xor_sync(0xffffffffu, s, 2);
                    k2 = max(k2, __float_as_int(s) & 0x7fffffff);
                }
#pragma unroll
                for (int m = 1; m < 32; m <<= 1) { k2 = imax_xor(k2, m); vm = imax_xor(vm, m); }
                if (lane == 0) *(int2*)(g_stat + blockIdx.x * 8) = make_int2(k2, vm);
                if (lane < 16) bulk_wait_all();
                __syncwarp();
                if (lane == 0) signal_add(&g_sync[SY_KV]);
                if (lane == 0) TS(12);
            }
        }
        bar_sync(1, 512);
        const uint32_t ring = sb + OFF_RING;
        const uint8_t* xn_src = g_xn + (size_t)rb * 16 * UNIT;
        auto issue1 = [&](int it) {
            const int pass = it > 8, kc = pass ? it - 9 : it;
            const uint32_t slot = ring + (it % 3) * 32768, bar = bars + BAR_R1 + (it % 3) * 8;
            mbar_expect(bar, pass ? 28672 : 32768);
            bulk_g2s(slot, xn_src + kc * 16384, 16384, bar);
            tma3(slot + 16384, pass ? &P.w1b : &P.w1a, bar, 0, kc * 64, 7 * c + 4 * pass);
        };
        if (prod) {
            if (lane == 0) TS(13);
            flag_wait(&g_sync[SY_KV], (epoch + 1) * 128);
            if (lane == 0) TS(14);
          if (elect()) {
            fence_async_all();
            l2_prefetch(P.w1p + blockIdx.x * 14336, 14336);
#pragma unroll
            for (int t = 0; t < 8; t++) {
                const uint32_t bar = bars + BAR_KV + 8 * t;
                mbar_expect(bar, t == 0 ? 17408 : 16384);
                if (t == 0) bulk_g2s(sb + OFF_STAT, g_stat, 1024, bar);
                bulk_g2s(sb + OFF_K + t * 8192, g_kv + t * 8192, 8192, bar);
                bulk_g2s(sb + OFF_V + t * 8192, g_kv + 65536 + t * 8192, 8192, bar);
                if (t == 1) { issue1(0); issue1(1); issue1(2); }
            }
            if (blockIdx.x == 0) asm volatile("st.relaxed.gpu.global.u32 [%0], %1;" ::"l"(&g_sync[SY_EPOCH]), "r"(epoch + 1) : "memory");
            l2_prefetch(P.w2p + blockIdx.x * 14336, 14336);
            l2_prefetch(P.wop + blockIdx.x * 4096, 4096);
          }
        }
        __syncwarp();
        uint8_t* h_dst = g_h + (size_t)(rb * 56 + 7 * c) * UNIT;
        {
            float c0[64], c1[64];
#pragma unroll
            for (int i = 0; i < 64; i++) { c0[i] = 0.f; c1[i] = 0.f; }
            pin(c0); pin(c1);
#pragma unroll 1
            for (int it = 0; it < 8; it++) {
                const int s = it % 3;
                mbar_wait(bars + BAR_R1 + s * 8, (it / 3) & 1);
                gemm_item(c0, c1, ring + s * 32768, ring + s * 32768 + 16384);
                wg_wait<1>();
                bar_sync(5, 128);
                if (prod && it >= 1 && it != 6 && elect()) issue1(it + 2);
                __syncwarp();
            }
            wg_wait<0>();
            pin(c0); pin(c1);
            stage_h<4>(c0, ring + 2 * 32768, wq4 * 16, lane);
            stage_h<4>(c1, ring + 2 * 32768, 64 + wq4 * 16, lane);
            fence_async_smem();
            bar_sync(5, 128);
            if (prod && elect()) {
                issue1(10);
                bulk_s2g(h_dst, ring + 2 * 32768, 4 * UNIT);
                bulk_commit();
                TS(15);
            }
            __syncwarp();
        }
        {
            float c0[48], c1[48];
#pragma unroll
            for (int i = 0; i < 48; i++) { c0[i] = 0.f; c1[i] = 0.f; }
            pin(c0); pin(c1);
#pragma unroll 1
            for (int it = 9; it < 17; it++) {
                const int s = it % 3;
                mbar_wait(bars + BAR_R1 + s * 8, ((it / 3) - (s == 2)) & 1);
                gemm_item(c0, c1, ring + s * 32768, ring + s * 32768 + 16384);
                wg_wait<1>();
                bar_sync(5, 128);
                if (prod && it < 15 && elect()) {
                    if (it == 9) bulk_wait_read();
                    issue1(it + 2);
                }
                __syncwarp();
            }
            wg_wait<0>();
            pin(c0); pin(c1);
            stage_h<3>(c0, ring + 2 * 32768, wq4 * 16, lane);
            stage_h<3>(c1, ring + 2 * 32768, 64 + wq4 * 16, lane);
            fence_async_smem();
            bar_sync(5, 128);
            if (prod && elect()) {
                bulk_s2g(h_dst + 4 * UNIT, ring + 2 * 32768, 3 * UNIT);
                bulk_commit();
                bulk_wait_all();
                signal_add(&g_sync[SY_H + rb * 32]);
                TS(16);
            }
            __syncwarp();
        }
        float c0[32], c1[32];
        {
            const __nv_bfloat16* xp = P.x + (size_t)(rb * 128 + wq4 * 16 + g) * DM + c * 64 + 2 * t4;
#pragma unroll
            for (int j = 0; j < 8; j++) {
                const uint32_t v0 = ldg_here(xp + 8 * j), v1 = ldg_here(xp + 8 * DM + 8 * j);
                const uint32_t v2 = ldg_here(xp + 64 * DM + 8 * j), v3 = ldg_here(xp + 72 * DM + 8 * j);
                c0[4 * j] = bf_lo(v0); c0[4 * j + 1] = bf_hi(v0); c0[4 * j + 2] = bf_lo(v1); c0[4 * j + 3] = bf_hi(v1);
                c1[4 * j] = bf_lo(v2); c1[4 * j + 1] = bf_hi(v2); c1[4 * j + 2] = bf_lo(v3); c1[4 * j + 3] = bf_hi(v3);
            }
            pin(c0); pin(c1);
        }
        constexpr int NIT = 36;
        const uint8_t* h_src = g_h + (size_t)rb * 56 * UNIT;
        const uint8_t* o_src = g_o + (size_t)rb * 16 * UNIT;
        auto head_of = [](int it) { const int p = (it - 28) >> 1; return p < 2 ? p : 5 - p; };
        auto gate = [&](int it, uint32_t& target) -> const uint32_t* {
            if (it == 0) { target = (epoch + 1) * 8; return &g_sync[SY_H + rb * 32]; }
            if (it >= 28 && !(it & 1)) { target = (epoch + 1) * 64; return &g_sync[SY_O + (rb * 4 + head_of(it)) * 32]; }
            return nullptr;
        };
        auto issue2 = [&](int it) {
            const uint32_t slot = ring + (it & 3) * 24576, bar = bars + BAR_R2 + (it & 3) * 8;
            mbar_expect(bar, 24576);
            if (it < 28) {
                tma3(slot + 16384, &P.w2, bar, 0, it * 64, 2 * c);
                bulk_g2s(slot, h_src + it * 16384, 16384, bar);
            } else {
                const int h = head_of(it);
                tma4(slot + 16384, &P.wo, bar, 0, 16 * h, 4 * (it & 1), 2 * c);
                bulk_g2s(slot, o_src + (h * 4 + 2 * (it & 1)) * UNIT, 16384, bar);
            }
        };
        int next = 0, it = 0;
#pragma unroll 1
        for (int seg = 0; seg < 5; seg++) {
            const int end = 28 + 2 * seg;
            if (prod && next == it) {
                uint32_t target;
                const uint32_t* f = gate(it, target);
                flag_wait(f, target);
                if (lane == 0) TS(17 + seg);
                if (elect()) {
                    fence_async_all();
                    issue2(it);
                    issue2(it + 1);
                    if (seg == 0) { issue2(2); issue2(3); }
                }
                __syncwarp();
                next = seg == 0 ? 4 : it + 2;
            }
#pragma unroll 1
            for (; it < end; it++) {
                mbar_wait(bars + BAR_R2 + (it & 3) * 8, (it >> 2) & 1);
                gemm_item(c0, c1, ring + (it & 3) * 24576, ring + (it & 3) * 24576 + 16384);
                wg_wait<1>();
                bar_sync(5, 128);
                if (prod) {
                    while (next < NIT && next < it + 4) {
                        uint32_t target;
                        const uint32_t* f = gate(next, target);
                        if (f && !flag_ready(f, target)) break;
                        if (elect()) { if (f) fence_async_all(); issue2(next); }
                        __syncwarp();
                        next++;
                    }
                }
            }
            wg_wait<0>();
            pin(c0); pin(c1);
        }
        if (tid == 384) TS(22);
        bar_sync(5, 128);
        {
            const int row = wq4 * 16 + ((lane >> 3) & 1) * 8 + (lane & 7);
#pragma unroll
            for (int j = 0; j < 8; j += 2) {
                const uint32_t a = ring + row * 128 + (((j + (lane >> 4)) ^ (row & 7)) << 4);
                stsm4(a, pack_bf16(c0[4 * j], c0[4 * j + 1]), pack_bf16(c0[4 * j + 2], c0[4 * j + 3]),
                      pack_bf16(c0[4 * j + 4], c0[4 * j + 5]), pack_bf16(c0[4 * j + 6], c0[4 * j + 7]));
                stsm4(a + 8192, pack_bf16(c1[4 * j], c1[4 * j + 1]), pack_bf16(c1[4 * j + 2], c1[4 * j + 3]),
                      pack_bf16(c1[4 * j + 4], c1[4 * j + 5]), pack_bf16(c1[4 * j + 6], c1[4 * j + 7]));
            }
            fence_async_smem();
            bar_sync(5, 128);
            if (prod && elect()) {
                tma2_store(&P.out, ring, c * 64, rb * 128);
                bulk_commit();
                bulk_wait_read();
                TS(23); TSG(61);
            }
        }
    }
}

typedef CUresult (*EncodeFn)(CUtensorMap*, CUtensorMapDataType, cuuint32_t, void*, const cuuint64_t*, const cuuint64_t*, const cuuint32_t*,
                             const cuuint32_t*, CUtensorMapInterleave, CUtensorMapSwizzle, CUtensorMapL2promotion, CUtensorMapFloatOOBfill);

void encode(EncodeFn fn, CUtensorMap* m, const void* p, int rank, const cuuint64_t* dims, const cuuint64_t* strides, const cuuint32_t* box, CUtensorMapSwizzle sw) {
    const cuuint32_t es[5] = {1, 1, 1, 1, 1};
    fn(m, CU_TENSOR_MAP_DATA_TYPE_BFLOAT16, rank, const_cast<void*>(p), dims, strides, box, es, CU_TENSOR_MAP_INTERLEAVE_NONE, sw,
       CU_TENSOR_MAP_L2_PROMOTION_L2_256B, CU_TENSOR_MAP_FLOAT_OOB_FILL_NONE);
}

}

extern "C" void kernel_launch(void* const* d_in, const int* in_sizes, int n_in, void* d_out, int out_size) {
    (void)in_sizes; (void)n_in; (void)out_size;
    static EncodeFn fn = nullptr;
    if (!fn) {
        void* p = nullptr;
        cudaDriverEntryPointQueryResult qr;
        cudaGetDriverEntryPoint("cuTensorMapEncodeTiled", &p, cudaEnableDefault, &qr);
        fn = (EncodeFn)p;
        cudaFuncSetAttribute(fused_mqa_ffn_kernel, cudaFuncAttributeMaxDynamicSharedMemorySize, SMEM_BYTES);
    }
    Params P;
    {
        const cuuint64_t d[3] = {16, 512, 32}, s[2] = {DM * 2, 32};
        const cuuint32_t b[3] = {16, 256, 4};
        encode(fn, &P.wq, d_in[1], 3, d, s, b, CU_TENSOR_MAP_SWIZZLE_32B);
    }
    {
        const cuuint64_t d[2] = {16, 512}, s[1] = {32};
        const cuuint32_t b[2] = {16, 256};
        encode(fn, &P.wk, d_in[2], 2, d, s, b, CU_TENSOR_MAP_SWIZZLE_32B);
        encode(fn, &P.wv, d_in[3], 2, d, s, b, CU_TENSOR_MAP_SWIZZLE_32B);
    }
    {
        const cuuint64_t d[3] = {32, 512, 56}, s[2] = {DFF * 2, 64};
        const cuuint32_t ba[3] = {32, 64, 4}, bb[3] = {32, 64, 3};
        encode(fn, &P.w1a, d_in[6], 3, d, s, ba, CU_TENSOR_MAP_SWIZZLE_64B);
        encode(fn, &P.w1b, d_in[6], 3, d, s, bb, CU_TENSOR_MAP_SWIZZLE_64B);
    }
    {
        const cuuint64_t d[3] = {32, DFF, 16}, s[2] = {DM * 2, 64};
        const cuuint32_t b[3] = {32, 64, 2};
        encode(fn, &P.w2, d_in[7], 3, d, s, b, CU_TENSOR_MAP_SWIZZLE_64B);
    }
    {
        const cuuint64_t d[4] = {32, 64, 8, 16}, s[3] = {DM * 2, 64 * DM * 2, 64};
        const cuuint32_t b[4] = {32, 16, 4, 2};
        encode(fn, &P.wo, d_in[4], 4, d, s, b, CU_TENSOR_MAP_SWIZZLE_64B);
    }
    {
        const cuuint64_t d[2] = {DM, SEQ}, s[1] = {DM * 2};
        const cuuint32_t b[2] = {64, 128};
        encode(fn, &P.out, d_out, 2, d, s, b, CU_TENSOR_MAP_SWIZZLE_128B);
    }
    P.x = (const __nv_bfloat16*)d_in[0];
    P.w1p = (const uint8_t*)d_in[6];
    P.w2p = (const uint8_t*)d_in[7];
    P.wop = (const uint8_t*)d_in[4];
    fused_mqa_ffn_kernel<<<128, 512, SMEM_BYTES, cudaStreamPerThread>>>(P);
}
```

```cpp
#include <cuda_runtime.h>
#include <cuda.h>
#include <cuda_bf16.h>
#include <cuda_fp16.h>
#include <stdint.h>
#include <utility>

namespace {

constexpr int SEQ = 2048, DM = 512, DFF = 1792;
#define POLY_MASK 0x33333333u
#define LN_PRIO 2
#define SPLIT_T 5
#define PVCH 1

constexpr int UNIT = 8192;
__device__ __align__(1024) uint8_t g_kv[131072];
__device__ __align__(1024) uint4   g_kvb[SEQ * 4];
__device__ __align__(1024) uint8_t g_xn[16 * 8 * 16384];
__device__ __align__(1024) uint8_t g_h[16 * 56 * UNIT];
__device__ __align__(1024) uint4   g_q[128 * 128];
__device__ __align__(1024) uint8_t g_o[16 * 16 * UNIT];
__device__ __align__(1024) uint32_t g_sync[32 * (2 + 16 + 64)];
constexpr int SY_EPOCH = 0, SY_KV = 1, SY_MAX = 4, SY_H = 64, SY_O = 64 + 16 * 32;
#define TS(i) do {} while (0)
#define TSG(i) do {} while (0)

constexpr uint32_t OFF_XN = 0;
constexpr uint32_t OFF_K = 0, OFF_V = 65536;
constexpr uint32_t OFF_ONES = 131072;
constexpr uint32_t OFF_RING = 132096;
constexpr uint32_t OFF_WQ = OFF_RING, OFF_WK = OFF_RING + 65536, OFF_WV = OFF_RING + 81920;
constexpr uint32_t OFF_MERGE = OFF_RING + 73728;
constexpr uint32_t OFF_STAT = OFF_RING + 98304;
constexpr uint32_t OFF_BAR = OFF_STAT + 1024;
constexpr uint32_t SMEM_BYTES = OFF_BAR + 768;
constexpr uint32_t BAR_WQ = 0, BAR_WKV = 8, BAR_KV = 16, BAR_R1 = 80, BAR_R2 = 104, BAR_X = 136, BAR_ST = 264, STAT_VAL = 272, BAR_OH = 280, BAR_O = 312;
constexpr int N_BARS = 17;

template <class F, int... I> __device__ __forceinline__ void static_for_impl(F&& f, std::integer_sequence<int, I...>) { (f(std::integral_constant<int, I>{}), ...); }
template <int N, class F> __device__ __forceinline__ void static_for(F&& f) { static_for_impl(f, std::make_integer_sequence<int, N>{}); }

__device__ __forceinline__ void wg_fence() { asm volatile("wgmma.fence.sync.aligned;" ::: "memory"); }
__device__ __forceinline__ void wg_commit() { asm volatile("wgmma.commit_group.sync.aligned;" ::: "memory"); }
template <int N> __device__ __forceinline__ void wg_wait() { asm volatile("wgmma.wait_group.sync.aligned %0;" ::"n"(N) : "memory"); }
__device__ __forceinline__ void pin(float& x) { asm volatile("" : "+f"(x)::"memory"); }
__device__ __forceinline__ void pin(uint32_t& x) { asm volatile("" : "+r"(x)::"memory"); }
template <class T, int N> __device__ __forceinline__ void pin(T (&d)[N]) {
#pragma unroll
    for (int i = 0; i < N; i++) pin(d[i]);
}
__device__ __forceinline__ uint64_t mkdesc(uint32_t addr, uint32_t lbo, uint32_t sbo, uint32_t sw) {
    return (uint64_t)((addr >> 4) | ((lbo >> 4) << 16)) | ((uint64_t)((sbo >> 4) | (sw << 30)) << 32);
}
__device__ __forceinline__ void mbar_init(uint32_t bar, int cnt) { asm volatile("mbarrier.init.shared::cta.b64 [%0], %1;" ::"r"(bar), "r"(cnt) : "memory"); }
__device__ __forceinline__ void mbar_expect(uint32_t bar, uint32_t bytes) { asm volatile("mbarrier.arrive.expect_tx.shared::cta.b64 _, [%0], %1;" ::"r"(bar), "r"(bytes) : "memory"); }
__device__ __forceinline__ bool mbar_try(uint32_t bar, uint32_t par) {
    uint32_t r;
    asm volatile("{.reg .pred p; mbarrier.try_wait.parity.shared::cta.b64 p, [%1], %2, %3; selp.u32 %0, 1, 0, p;}" : "=r"(r) : "r"(bar), "r"(par), "r"(20000u) : "memory");
    return r;
}
__device__ __forceinline__ void mbar_wait(uint32_t bar, uint32_t par) {
    int n = 0;
    while (!__all_sync(0xffffffffu, mbar_try(bar, par) | (++n > (1 << 16)))) {}
}
__device__ __forceinline__ bool elect() {
    uint32_t r;
    asm volatile("{.reg .pred p; elect.sync _|p, 0xffffffff; selp.u32 %0, 1, 0, p;}" : "=r"(r));
    return r;
}
__device__ __forceinline__ void bulk_g2s(uint32_t dst, const void* src, uint32_t bytes, uint32_t bar) {
    asm volatile("cp.async.bulk.shared::cluster.global.mbarrier::complete_tx::bytes [%0], [%1], %2, [%3];" ::"r"(dst), "l"(src), "r"(bytes), "r"(bar) : "memory");
}
__device__ __forceinline__ void bulk_s2g(void* dst, uint32_t src, uint32_t bytes) {
    asm volatile("cp.async.bulk.global.shared::cta.bulk_group [%0], [%1], %2;" ::"l"(dst), "r"(src), "r"(bytes) : "memory");
}
__device__ __forceinline__ void bulk_commit() { asm volatile("cp.async.bulk.commit_group;" ::: "memory"); }
__device__ __forceinline__ void bulk_wait_all() { asm volatile("cp.async.bulk.wait_group 0;" ::: "memory"); }
__device__ __forceinline__ void bulk_wait_read() { asm volatile("cp.async.bulk.wait_group.read 0;" ::: "memory"); }
__device__ __forceinline__ void l2_prefetch(const void* p, uint32_t bytes) { asm volatile("cp.async.bulk.prefetch.L2.global [%0], %1;" ::"l"(p), "r"(bytes) : "memory"); }
__device__ __forceinline__ void tma2(uint32_t dst, const CUtensorMap* m, uint32_t bar, int c0, int c1) {
    asm volatile("cp.async.bulk.tensor.2d.shared::cluster.global.mbarrier::complete_tx::bytes [%0], [%1, {%3, %4}], [%2];" ::"r"(dst), "l"(m), "r"(bar), "r"(c0), "r"(c1) : "memory");
}
__device__ __forceinline__ void tma3(uint32_t dst, const CUtensorMap* m, uint32_t bar, int c0, int c1, int c2) {
    asm volatile("cp.async.bulk.tensor.3d.shared::cluster.global.mbarrier::complete_tx::bytes [%0], [%1, {%3, %4, %5}], [%2];" ::"r"(dst), "l"(m), "r"(bar), "r"(c0), "r"(c1), "r"(c2) : "memory");
}
__device__ __forceinline__ void tma2_store(const CUtensorMap* m, uint32_t src, int c0, int c1) {
    asm volatile("cp.async.bulk.tensor.2d.global.shared::cta.bulk_group [%0, {%2, %3}], [%1];" ::"l"(m), "r"(src), "r"(c0), "r"(c1) : "memory");
}
__device__ __forceinline__ void prefetch_map(const CUtensorMap* m) { asm volatile("prefetch.tensormap [%0];" ::"l"(m) : "memory"); }
__device__ __forceinline__ void fence_async_smem() { asm volatile("fence.proxy.async.shared::cta;" ::: "memory"); }
__device__ __forceinline__ void fence_async_global() { asm volatile("fence.proxy.async.global;" ::: "memory"); }
__device__ __forceinline__ void bar_sync(int id, int n) { asm volatile("bar.sync %0, %1;" ::"r"(id), "r"(n) : "memory"); }
__device__ __forceinline__ void bar_arrive(int id, int n) { asm volatile("bar.arrive %0, %1;" ::"r"(id), "r"(n) : "memory"); }
__device__ __forceinline__ bool bar_or(int id, int n, bool p) {
    uint32_t r;
    asm volatile("{.reg .pred a, b; setp.ne.u32 a, %3, 0; bar.red.or.pred b, %1, %2, a; selp.u32 %0, 1, 0, b;}" : "=r"(r) : "r"(id), "r"(n), "r"((uint32_t)p) : "memory");
    return r;
}
__device__ __forceinline__ void signal_add(uint32_t* p) {
    asm volatile("red.release.gpu.global.add.u32 [%0], 1;" ::"l"(p) : "memory");
}
__device__ __forceinline__ void flag_wait(const uint32_t* p, uint32_t target) {
    int n = 0;
    uint32_t v;
    do {
        asm volatile("ld.relaxed.gpu.global.u32 %0, [%1];" : "=r"(v) : "l"(p) : "memory");
    } while (!__all_sync(0xffffffffu, ((int)(v - target) >= 0) | (++n > (1 << 21))));
    asm volatile("fence.acquire.gpu;" ::: "memory");
}
__device__ __forceinline__ void stsm4(uint32_t addr, uint32_t r0, uint32_t r1, uint32_t r2, uint32_t r3) {
    asm volatile("stmatrix.sync.aligned.m8n8.x4.shared.b16 [%0], {%1, %2, %3, %4};" ::"r"(addr), "r"(r0), "r"(r1), "r"(r2), "r"(r3) : "memory");
}
__device__ __forceinline__ uint32_t pack_bf16(float lo, float hi) { uint32_t d; asm("cvt.rn.bf16x2.f32 %0, %1, %2;" : "=r"(d) : "f"(hi), "f"(lo)); return d; }
__device__ __forceinline__ uint32_t pack_bf16_relu(float lo, float hi) { uint32_t d; asm("cvt.rn.relu.bf16x2.f32 %0, %1, %2;" : "=r"(d) : "f"(hi), "f"(lo)); return d; }
__device__ __forceinline__ uint32_t pack_f16(float lo, float hi) { uint32_t d; asm("cvt.rn.f16x2.f32 %0, %1, %2;" : "=r"(d) : "f"(hi), "f"(lo)); return d; }
__device__ __forceinline__ float bf_lo(uint32_t v) { return __uint_as_float(v << 16); }
__device__ __forceinline__ float bf_hi(uint32_t v) { return __uint_as_float(v & 0xffff0000u); }
__device__ __forceinline__ float bf_round(float x) { return bf_lo(pack_bf16(x, 0.f)); }
__device__ __forceinline__ uint32_t bf2fma(uint32_t a, uint32_t b, uint32_t c) { uint32_t d; asm("fma.rn.bf16x2 %0, %1, %2, %3;" : "=r"(d) : "r"(a), "r"(b), "r"(c)); return d; }
__device__ __forceinline__ uint32_t h2fma(uint32_t a, uint32_t b, uint32_t c) { uint32_t d; asm("fma.rn.f16x2 %0, %1, %2, %3;" : "=r"(d) : "r"(a), "r"(b), "r"(c)); return d; }
__device__ __forceinline__ uint32_t h2fma_sat(uint32_t a, uint32_t b, uint32_t c) { uint32_t d; asm("fma.rn.sat.f16x2 %0, %1, %2, %3;" : "=r"(d) : "r"(a), "r"(b), "r"(c)); return d; }
__device__ __forceinline__ uint32_t h2sub(uint32_t a, uint32_t b) { uint32_t d; asm("sub.f16x2 %0, %1, %2;" : "=r"(d) : "r"(a), "r"(b)); return d; }
__device__ __forceinline__ uint32_t h2mul(uint32_t a, uint32_t b) { uint32_t d; asm("mul.f16x2 %0, %1, %2;" : "=r"(d) : "r"(a), "r"(b)); return d; }
__device__ __forceinline__ uint32_t h2max(uint32_t a, uint32_t b) { uint32_t d; asm("max.f16x2 %0, %1, %2;" : "=r"(d) : "r"(a), "r"(b)); return d; }
__device__ __forceinline__ uint32_t h2min(uint32_t a, uint32_t b) { uint32_t d; asm("min.f16x2 %0, %1, %2;" : "=r"(d) : "r"(a), "r"(b)); return d; }
__device__ __forceinline__ uint32_t h2ex2(uint32_t a) { uint32_t d; asm("ex2.approx.f16x2 %0, %1;" : "=r"(d) : "r"(a)); return d; }
__device__ __forceinline__ uint32_t prmt(uint32_t a, uint32_t b, uint32_t s) { uint32_t d; asm("prmt.b32 %0, %1, %2, %3;" : "=r"(d) : "r"(a), "r"(b), "r"(s)); return d; }
__device__ __forceinline__ float ex2f(float a) { float d; asm("ex2.approx.ftz.f32 %0, %1;" : "=f"(d) : "f"(a)); return d; }
__device__ __forceinline__ float sqrt_fast(float a) { float d; asm("sqrt.approx.f32 %0, %1;" : "=f"(d) : "f"(a)); return d; }
__device__ __forceinline__ float rcp_fast(float a) { float d; asm("rcp.approx.f32 %0, %1;" : "=f"(d) : "f"(a)); return d; }
__device__ __forceinline__ float h_lo(uint32_t a) { float d; asm("{.reg .b16 l, h; mov.b32 {l, h}, %1; cvt.f32.f16 %0, l;}" : "=f"(d) : "r"(a)); return d; }
__device__ __forceinline__ float h_hi(uint32_t a) { float d; asm("{.reg .b16 l, h; mov.b32 {l, h}, %1; cvt.f32.f16 %0, h;}" : "=f"(d) : "r"(a)); return d; }
__device__ __forceinline__ uint32_t bc_lo(uint32_t a) { uint32_t d; asm("{.reg .b16 l, h; mov.b32 {l, h}, %1; mov.b32 %0, {l, l};}" : "=r"(d) : "r"(a)); return d; }
__device__ __forceinline__ uint32_t bc_hi(uint32_t a) { uint32_t d; asm("{.reg .b16 l, h; mov.b32 {l, h}, %1; mov.b32 %0, {h, h};}" : "=r"(d) : "r"(a)); return d; }
__device__ __forceinline__ uint32_t ldg_here(const void* p) { uint32_t v; asm volatile("ld.global.nc.u32 %0, [%1];" : "=r"(v) : "l"(p) : "memory"); return v; }
__device__ __forceinline__ int imax_xor(int v, int m) { return max(v, __shfl_xor_sync(0xffffffffu, v, m)); }

__device__ __forceinline__ void wgmma_qk(uint32_t (&d)[64], const uint32_t (&a)[4], uint64_t bdesc) {
    asm volatile("wgmma.mma_async.sync.aligned.m64n256k16.f16.f16.f16 {"
        "%0, %1, %2, %3, %4, %5, %6, %7, %8, %9, %10, %11, %12, %13, %14, %15, "
        "%16, %17, %18, %19, %20, %21, %22, %23, %24, %25, %26, %27, %28, %29, %30, %31, "
        "%32, %33, %34, %35, %36, %37, %38, %39, %40, %41, %42, %43, %44, %45, %46, %47, "
        "%48, %49, %50, %51, %52, %53, %54, %55, %56, %57, %58, %59, %60, %61, %62, %63"
        "}, {%64, %65, %66, %67}, %68, 0, 1, 1, 0;\n"
        : "=r"(d[0]), "=r"(d[1]), "=r"(d[2]), "=r"(d[3]), "=r"(d[4]), "=r"(d[5]), "=r"(d[6]), "=r"(d[7]),
          "=r"(d[8]), "=r"(d[9]), "=r"(d[10]), "=r"(d[11]), "=r"(d[12]), "=r"(d[13]), "=r"(d[14]), "=r"(d[15]),
          "=r"(d[16]), "=r"(d[17]), "=r"(d[18]), "=r"(d[19]), "=r"(d[20]), "=r"(d[21]), "=r"(d[22]), "=r"(d[23]),
          "=r"(d[24]), "=r"(d[25]), "=r"(d[26]), "=r"(d[27]), "=r"(d[28]), "=r"(d[29]), "=r"(d[30]), "=r"(d[31]),
          "=r"(d[32]), "=r"(d[33]), "=r"(d[34]), "=r"(d[35]), "=r"(d[36]), "=r"(d[37]), "=r"(d[38]), "=r"(d[39]),
          "=r"(d[40]), "=r"(d[41]), "=r"(d[42]), "=r"(d[43]), "=r"(d[44]), "=r"(d[45]), "=r"(d[46]), "=r"(d[47]),
          "=r"(d[48]), "=r"(d[49]), "=r"(d[50]), "=r"(d[51]), "=r"(d[52]), "=r"(d[53]), "=r"(d[54]), "=r"(d[55]),
          "=r"(d[56]), "=r"(d[57]), "=r"(d[58]), "=r"(d[59]), "=r"(d[60]), "=r"(d[61]), "=r"(d[62]), "=r"(d[63])
        : "r"(a[0]), "r"(a[1]), "r"(a[2]), "r"(a[3]), "l"(bdesc));
}
__device__ __forceinline__ void wgmma_pv(float (&d)[12], uint32_t a0, uint32_t a1, uint32_t a2, uint32_t a3, uint64_t bdesc) {
    asm volatile("wgmma.mma_async.sync.aligned.m64n24k16.f32.f16.f16 {"
        "%0, %1, %2, %3, %4, %5, %6, %7, %8, %9, %10, %11"
        "}, {%12, %13, %14, %15}, %16, 1, 1, 1, 1;\n"
        : "+f"(d[0]), "+f"(d[1]), "+f"(d[2]), "+f"(d[3]), "+f"(d[4]), "+f"(d[5]), "+f"(d[6]), "+f"(d[7]),
          "+f"(d[8]), "+f"(d[9]), "+f"(d[10]), "+f"(d[11])
        : "r"(a0), "r"(a1), "r"(a2), "r"(a3), "l"(bdesc));
}
__device__ __forceinline__ void wgmma_ss(float (&d)[16], uint64_t adesc, uint64_t bdesc) {
    asm volatile("wgmma.mma_async.sync.aligned.m64n32k16.f32.bf16.bf16 {"
        "%0, %1, %2, %3, %4, %5, %6, %7, %8, %9, %10, %11, %12, %13, %14, %15"
        "}, %16, %17, 1, 1, 1, 0, 1;\n"
        : "+f"(d[0]), "+f"(d[1]), "+f"(d[2]), "+f"(d[3]), "+f"(d[4]), "+f"(d[5]), "+f"(d[6]), "+f"(d[7]),
          "+f"(d[8]), "+f"(d[9]), "+f"(d[10]), "+f"(d[11]), "+f"(d[12]), "+f"(d[13]), "+f"(d[14]), "+f"(d[15])
        : "l"(adesc), "l"(bdesc));
}
__device__ __forceinline__ void wgmma_ss(float (&d)[32], uint64_t adesc, uint64_t bdesc) {
    asm volatile("wgmma.mma_async.sync.aligned.m64n64k16.f32.bf16.bf16 {"
        "%0, %1, %2, %3, %4, %5, %6, %7, %8, %9, %10, %11, %12, %13, %14, %15, "
        "%16, %17, %18, %19, %20, %21, %22, %23, %24, %25, %26, %27, %28, %29, %30, %31"
        "}, %32, %33, 1, 1, 1, 0, 1;\n"
        : "+f"(d[0]), "+f"(d[1]), "+f"(d[2]), "+f"(d[3]), "+f"(d[4]), "+f"(d[5]), "+f"(d[6]), "+f"(d[7]),
          "+f"(d[8]), "+f"(d[9]), "+f"(d[10]), "+f"(d[11]), "+f"(d[12]), "+f"(d[13]), "+f"(d[14]), "+f"(d[15]),
          "+f"(d[16]), "+f"(d[17]), "+f"(d[18]), "+f"(d[19]), "+f"(d[20]), "+f"(d[21]), "+f"(d[22]), "+f"(d[23]),
          "+f"(d[24]), "+f"(d[25]), "+f"(d[26]), "+f"(d[27]), "+f"(d[28]), "+f"(d[29]), "+f"(d[30]), "+f"(d[31])
        : "l"(adesc), "l"(bdesc));
}
__device__ __forceinline__ void wgmma_ss(float (&d)[48], uint64_t adesc, uint64_t bdesc) {
    asm volatile("wgmma.mma_async.sync.aligned.m64n96k16.f32.bf16.bf16 {"
        "%0, %1, %2, %3, %4, %5, %6, %7, %8, %9, %10, %11, %12, %13, %14, %15, "
        "%16, %17, %18, %19, %20, %21, %22, %23, %24, %25, %26, %27, %28, %29, %30, %31, "
        "%32, %33, %34, %35, %36, %37, %38, %39, %40, %41, %42, %43, %44, %45, %46, %47"
        "}, %48, %49, 1, 1, 1, 0, 1;\n"
        : "+f"(d[0]), "+f"(d[1]), "+f"(d[2]), "+f"(d[3]), "+f"(d[4]), "+f"(d[5]), "+f"(d[6]), "+f"(d[7]),
          "+f"(d[8]), "+f"(d[9]), "+f"(d[10]), "+f"(d[11]), "+f"(d[12]), "+f"(d[13]), "+f"(d[14]), "+f"(d[15]),
          "+f"(d[16]), "+f"(d[17]), "+f"(d[18]), "+f"(d[19]), "+f"(d[20]), "+f"(d[21]), "+f"(d[22]), "+f"(d[23]),
          "+f"(d[24]), "+f"(d[25]), "+f"(d[26]), "+f"(d[27]), "+f"(d[28]), "+f"(d[29]), "+f"(d[30]), "+f"(d[31]),
          "+f"(d[32]), "+f"(d[33]), "+f"(d[34]), "+f"(d[35]), "+f"(d[36]), "+f"(d[37]), "+f"(d[38]), "+f"(d[39]),
          "+f"(d[40]), "+f"(d[41]), "+f"(d[42]), "+f"(d[43]), "+f"(d[44]), "+f"(d[45]), "+f"(d[46]), "+f"(d[47])
        : "l"(adesc), "l"(bdesc));
}

#define H2C(x) ((uint32_t)(x) * 0x00010001u)
constexpr uint32_t C_2M15 = H2C(0x0200), C_N2M15 = H2C(0x8200), C_2P15 = H2C(0x7800), C_N2P15 = H2C(0xF800);
constexpr uint32_t C_512 = H2C(0x6000), C_N512 = H2C(0xE000), C_OFF27 = H2C(27), C_N13P5 = H2C(0xCAC0);
constexpr uint32_t PC0 = H2C(0x05a8), PC1 = H2C(0x27d9), PC2 = H2C(0x4581), PC3 = H2C(0x60ea);
constexpr float Q_SCALE = 0.25f * 1.4426950408889634f;

__device__ __forceinline__ uint32_t exp_mufu(uint32_t s, uint32_t cx) { return h2ex2(h2fma(s, C_512, cx)); }
__device__ __forceinline__ uint32_t exp_fma(uint32_t s, uint32_t cr, uint32_t ct, uint32_t z) {
    const uint32_t r = h2fma_sat(s, C_2M15, cr);
    const uint32_t t = h2fma(r, C_2P15, ct);
    const uint32_t f = h2sub(s, t);
    uint32_t p = h2fma(f, PC3, PC2);
    p = h2fma(p, f, PC1);
    p = h2fma_sat(p, f, PC0);
    uint32_t e;
    asm("shf.l.wrap.b32 %0, %1, %2, 10;" : "=r"(e) : "r"(z), "r"(r));
    return e + p;
}
__host__ __device__ constexpr bool is_poly(int i) { return (POLY_MASK >> (i & 31)) & 1; }

constexpr long long K_INC = 512;
constexpr long long V_INC = 32 - (32 << 16);

__device__ __forceinline__ void attn_tile(float (&O)[12], const uint32_t (&q)[4], uint32_t& mrun, uint32_t& cxp, uint64_t kd, uint64_t vd, uint32_t z) {
    uint32_t S[64];
    wg_fence();
    wgmma_qk(S, q, kd);
    wg_commit();
    wg_wait<0>();
    pin(S);
    uint32_t ma = h2max(S[0], S[2]), mb = h2max(S[1], S[3]), mc = h2max(S[4], S[6]), md = h2max(S[5], S[7]);
#pragma unroll
    for (int i = 8; i < 64; i += 8) {
        ma = h2max(h2max(ma, S[i]), S[i + 2]);
        mb = h2max(h2max(mb, S[i + 1]), S[i + 3]);
        mc = h2max(h2max(mc, S[i + 4]), S[i + 6]);
        md = h2max(h2max(md, S[i + 5]), S[i + 7]);
    }
    uint32_t m = h2max(h2max(prmt(ma, mb, 0x5410), prmt(ma, mb, 0x7632)), h2max(prmt(mc, md, 0x5410), prmt(mc, md, 0x7632)));
    m = h2max(m, __shfl_xor_sync(0xffffffffu, m, 1));
    m = h2max(h2max(m, mrun), __shfl_xor_sync(0xffffffffu, m, 2));
    mrun = m;
    const uint32_t cr = h2fma(m, C_N2M15, C_OFF27);
    const uint32_t ct = h2mul(cr, C_N2P15);
    const uint32_t cx = h2fma(ct, C_N512, C_N13P5);
    const uint32_t dd = h2sub(cx, cxp);
    cxp = cx;
    const float a0 = ex2f(h_lo(dd)), a1 = ex2f(h_hi(dd));
    const uint32_t crA = bc_lo(cr), crB = bc_hi(cr), ctA = bc_lo(ct), ctB = bc_hi(ct), cxA = bc_lo(cx), cxB = bc_hi(cx);
#pragma unroll
    for (int i = 0; i < 12; i++) O[i] *= (i & 2) ? a1 : a0;
    static_for<16 / PVCH>([&](auto c) {
        constexpr int C = decltype(c)::value;
#pragma unroll
        for (int i = 4 * PVCH * C; i < 4 * PVCH * (C + 1); i++) {
            if (is_poly(i)) S[i] = exp_fma(S[i], (i & 1) ? crB : crA, (i & 1) ? ctB : ctA, z);
            else            S[i] = exp_mufu(S[i], (i & 1) ? cxB : cxA);
        }
        wg_fence();
#pragma unroll
        for (int k = PVCH * C; k < PVCH * (C + 1); k++) wgmma_pv(O, S[4 * k], S[4 * k + 1], S[4 * k + 2], S[4 * k + 3], vd + k * V_INC);
    });
    wg_commit();
    wg_wait<0>();
    pin(O);
}

__device__ __forceinline__ void attn_slow(const uint32_t (&qb)[12], uint8_t* ounit, int r0, int chunk0, int lane) {
    const int row = lane >> 1, half = lane & 1;
    float qf[16];
#pragma unroll
    for (int d = 0; d < 16; d += 2) {
        const int src = 4 * (row & 7) + ((d & 7) >> 1);
        const uint32_t v0 = __shfl_sync(0xffffffffu, qb[(d >> 3) * 2], src), v1 = __shfl_sync(0xffffffffu, qb[(d >> 3) * 2 + 1], src);
        const uint32_t w = (row & 8) ? v1 : v0;
        qf[d] = bf_lo(w) * Q_SCALE;
        qf[d + 1] = bf_hi(w) * Q_SCALE;
    }
    float m = -INFINITY, l = 0.f, o[16];
#pragma unroll
    for (int d = 0; d < 16; d++) o[d] = 0.f;
#pragma unroll 1
    for (int j = half * 1024; j < half * 1024 + 1024; j++) {
        uint32_t kv[16];
#pragma unroll
        for (int i = 0; i < 4; i++) {
            const uint4 t = __ldcg(&g_kvb[j * 4 + i]);
            kv[4 * i] = t.x; kv[4 * i + 1] = t.y; kv[4 * i + 2] = t.z; kv[4 * i + 3] = t.w;
        }
        float s = 0.f;
#pragma unroll
        for (int i = 0; i < 8; i++) {
            const uint32_t w = kv[4 * (i & 3) + (i >> 2)];
            s = fmaf(qf[2 * i + 1], bf_hi(w), fmaf(qf[2 * i], bf_lo(w), s));
        }
        const float mn = fmaxf(m, s), a = exp2f(m - mn), p = exp2f(s - mn);
        m = mn;
        l = fmaf(l, a, p);
#pragma unroll
        for (int i = 0; i < 8; i++) {
            const uint32_t w = kv[4 * (i & 3) + 2 + (i >> 2)];
            o[2 * i] = fmaf(o[2 * i], a, p * bf_lo(w));
            o[2 * i + 1] = fmaf(o[2 * i + 1], a, p * bf_hi(w));
        }
    }
    const float m2 = __shfl_xor_sync(0xffffffffu, m, 1), mn = fmaxf(m, m2), a = exp2f(m - mn);
    l *= a;
    l += __shfl_xor_sync(0xffffffffu, l, 1);
    const float inv = 1.f / l;
    uint32_t w[8];
#pragma unroll
    for (int i = 0; i < 8; i++) {
        float e0 = o[2 * i] * a, e1 = o[2 * i + 1] * a;
        e0 += __shfl_xor_sync(0xffffffffu, e0, 1);
        e1 += __shfl_xor_sync(0xffffffffu, e1, 1);
        w[i] = pack_bf16(e0 * inv, e1 * inv);
    }
    const int R = r0 + row;
    const uint4 val = half ? make_uint4(w[4], w[5], w[6], w[7]) : make_uint4(w[0], w[1], w[2], w[3]);
    *(uint4*)(ounit + R * 64 + (((chunk0 + half) ^ ((R >> 1) & 3)) << 4)) = val;
}

template <bool A128, int NR>
__device__ __forceinline__ void gemm_item(float (&c0)[NR], float (&c1)[NR], uint32_t a, uint32_t b) {
    const uint64_t ad = A128 ? mkdesc(a, 16, 1024, 1) : mkdesc(a, 16, 512, 2), bd = mkdesc(b, 8192, 1024, 1);
    wg_fence();
#pragma unroll
    for (int k = 0; k < 4; k++) {
        const int ka = A128 ? 2 * k : (k >> 1) * 512 + (k & 1) * 2;
        wgmma_ss(c0, ad + ka, bd + k * 128);
        wgmma_ss(c1, ad + ka + (A128 ? 512 : 256), bd + k * 128);
    }
    wg_commit();
}
template <int NU>
__device__ __forceinline__ void stage_h(const float (&c)[NU * 16], uint32_t dst, int row0, int lane) {
    const int row = row0 + ((lane >> 3) & 1) * 8 + (lane & 7), sw = (row >> 1) & 3;
#pragma unroll
    for (int j = 0; j < NU * 4; j += 2)
        stsm4(dst + (j >> 2) * UNIT + row * 64 + ((((j & 3) + (lane >> 4)) ^ sw) << 4),
              pack_bf16_relu(c[4 * j], c[4 * j + 1]), pack_bf16_relu(c[4 * j + 2], c[4 * j + 3]),
              pack_bf16_relu(c[4 * j + 4], c[4 * j + 5]), pack_bf16_relu(c[4 * j + 6], c[4 * j + 7]));
}

struct Params {
    const __nv_bfloat16* x;
    const uint8_t *wkp, *wvp, *w1p, *w2p, *wop;
    CUtensorMap wq, w1, w2, wo, out;
};

__global__ void __launch_bounds__(512, 1) fused_mqa_ffn_kernel(const __grid_constant__ Params P) {
    extern __shared__ __align__(1024) uint8_t smem[];
    const uint32_t sb = (uint32_t)__cvta_generic_to_shared(smem);
#define TID_ROT 0
    const int tid = (threadIdx.x + TID_ROT) & 511, lane = tid & 31, g = lane >> 2, t4 = lane & 3;
    const int warp = __shfl_sync(0xffffffffu, tid >> 5, 0), wg = warp >> 2, wq4 = warp & 3;
    const int rb = blockIdx.x >> 3, c = blockIdx.x & 7;
    const uint32_t bars = sb + OFF_BAR;
    if (tid == 0) { TS(0); TSG(60); }

    const int rg = (warp + 2 * c + 4) & 15;
    const uint32_t xb = sb + OFF_XN + rg * 8192, xbar = bars + BAR_X + 8 * warp;
    uint32_t epoch = 0;
    if (tid == 384) TS(36);
    if (wg < 3) bar_sync(7, 512);
    if (elect()) {
        mbar_init(xbar, 1);
        if (warp == 14) mbar_init(bars + BAR_WKV, 1);
        asm volatile("fence.mbarrier_init.release.cluster;" ::: "memory");
        mbar_expect(xbar, 8192);
        bulk_g2s(xb, (const uint8_t*)P.x + (size_t)rb * 131072 + rg * 8192, 8192, xbar);
        if (warp == 14) {
            mbar_expect(bars + BAR_WKV, 32768);
            bulk_g2s(sb + OFF_WK, P.wkp, 16384, bars + BAR_WKV);
            bulk_g2s(sb + OFF_WV, P.wvp, 16384, bars + BAR_WKV);
            TS(39);
        }
    }
    __syncwarp();
    if (wg == 3) {
        bar_arrive(7, 512);
        if (warp == 15 && elect()) {
            mbar_init(bars + BAR_WQ, 1);
            mbar_init(bars + BAR_ST, 1);
#pragma unroll
            for (int i = 0; i < 4; i++) mbar_init(bars + BAR_OH + 8 * i, 8);
#pragma unroll
            for (int i = 0; i < 8; i++) mbar_init(bars + BAR_O + 8 * i, 1);
#pragma unroll
            for (int i = 2; i < N_BARS; i++) mbar_init(bars + 8 * i, 1);
            asm volatile("fence.mbarrier_init.release.cluster;" ::: "memory");
        }
        asm volatile("ld.relaxed.gpu.global.u32 %0, [%1];" : "=r"(epoch) : "l"(&g_sync[SY_EPOCH]) : "memory");
        *(uint32_t*)(smem + OFF_ONES + 4 * (tid - 384)) = 0x3c003c00u;
        bar_sync(5, 128);
        mbar_wait(bars + BAR_WKV, 0);
        if (tid == 384) TS(26);
#pragma unroll
        for (int i = 0; i < 4; i++) {
            const int r = tid - 384 + 128 * i;
            uint4* p = (uint4*)(smem + OFF_WK + ((r >> 2) * 8 + 4 + (r & 3)) * 32);
            const uint4 u = p[0], v = p[1];
            p[0] = v; p[1] = u;
        }
    }
    {
        uint4 xv[16];
        mbar_wait(xbar, 0);
        if (tid == 0) TS(42);
        if (tid == 384) TS(40);
        if (tid == 352) TS(43);
        if (warp == 15 && elect()) {
            mbar_expect(bars + BAR_WQ, 65536);
            tma2(sb + OFF_WQ, &P.wq, bars + BAR_WQ, 64 * c, 0);
            tma2(sb + OFF_WQ + 32768, &P.wq, bars + BAR_WQ, 64 * c, 256);
        }
        __syncwarp();
#pragma unroll
        for (int i = 0; i < 16; i++)
            asm volatile("ld.shared.v4.b32 {%0, %1, %2, %3}, [%4];" : "=r"(xv[i].x), "=r"(xv[i].y), "=r"(xv[i].z), "=r"(xv[i].w)
                         : "r"(xb + g * 1024 + ((i ^ (g & 1)) * 64) + t4 * 16) : "memory");
        float acc[4][4];
#pragma unroll
        for (int i = 0; i < 4; i++)
#pragma unroll
            for (int j = 0; j < 4; j++) acc[i][j] = 0.f;
#pragma unroll
        for (int i = 0; i < 32; i++) {
            const uint32_t w0 = (i & 1) ? xv[i >> 1].z : xv[i >> 1].x, w1 = (i & 1) ? xv[i >> 1].w : xv[i >> 1].y;
            asm volatile("mma.sync.aligned.m16n8k16.row.col.f32.bf16.bf16.f32 {%0, %1, %2, %3}, {%4, %6, %5, %6}, {%4, %5}, {%0, %1, %2, %3};"
                         : "+f"(acc[i & 3][0]), "+f"(acc[i & 3][1]), "+f"(acc[i & 3][2]), "+f"(acc[i & 3][3])
                         : "r"(w0), "r"(w1), "r"(0x3f803f80u));
        }
        if (tid == 0) TS(27);
        float ssq = (g & 1) ? (acc[0][1] + acc[1][1]) + (acc[2][1] + acc[3][1]) : (acc[0][0] + acc[1][0]) + (acc[2][0] + acc[3][0]);
        float sum = (g & 1) ? (acc[0][3] + acc[1][3]) + (acc[2][3] + acc[3][3]) : (acc[0][2] + acc[1][2]) + (acc[2][2] + acc[3][2]);
        ssq = __shfl_sync(0xffffffffu, ssq, 4 * g + (g >> 1));
        sum = __shfl_sync(0xffffffffu, sum, 4 * g + (g >> 1));
        const float mean = sum * (1.f / DM);
        const float var = fmaxf(fmaf(-mean, mean, ssq * (1.f / DM)), 0.f);
        const float sd = bf_round(sqrt_fast(bf_round(bf_round(var) + 1e-5f)));
        const float r = rcp_fast(sd), rh = bf_round(r), cm = -bf_round(mean) * r;
        const uint32_t rhi = pack_bf16(rh, rh), rlo = pack_bf16(r - rh, r - rh), cc = pack_bf16(cm, cm);
        if (tid == 0) TS(1);
        if (wg < 3) bar_sync(10, 512);
        const uint32_t dst0 = xb + g * 128 + (((((g & 1) << 2) + t4) ^ g) << 4);
#pragma unroll
        for (int i = 0; i < 16; i++) {
            const uint32_t y0 = bf2fma(xv[i].x, rhi, bf2fma(xv[i].x, rlo, cc)), y1 = bf2fma(xv[i].y, rhi, bf2fma(xv[i].y, rlo, cc));
            const uint32_t y2 = bf2fma(xv[i].z, rhi, bf2fma(xv[i].z, rlo, cc)), y3 = bf2fma(xv[i].w, rhi, bf2fma(xv[i].w, rlo, cc));
            asm volatile("st.shared.v4.b32 [%0], {%1, %2, %3, %4};" ::"r"((dst0 ^ ((i & 1) << 6)) + (i >> 1) * 1024), "r"(y0), "r"(y1), "r"(y2), "r"(y3) : "memory");
        }
    }
    if (wg == 3) bar_arrive(10, 512);
    fence_async_smem();
    if (tid == 0) TS(2);

    if (wg < 3) {
        uint32_t qb[12];
        bar_sync(6, 512);
        if (tid == 0) TS(30);
        const uint32_t qx = sb + OFF_WK + (tid & 127) * 16;
        if (wg < 2) {
            mbar_wait(bars + BAR_WQ, 0);
            if (tid == 0) TS(31);
            float a[32];
#pragma unroll
            for (int i = 0; i < 32; i++) a[i] = 0.f;
            pin(a);
            const uint64_t ad = mkdesc(sb + OFF_XN + wg * 65536, 16, 8192, 1), bd = mkdesc(sb + OFF_WQ, 16, 1024, 1);
            wg_fence();
#pragma unroll
            for (int k = 0; k < 32; k++) wgmma_ss(a, ad + (k >> 2) * 64 + (k & 3) * 2, bd + k * 128);
            wg_commit();
            wg_wait<0>();
            pin(a);
            bar_sync(9, 384);
            asm volatile("st.shared.v4.b32 [%0], {%1, %2, %3, %4};" ::"r"(qx + wg * 2048), "r"(pack_bf16(a[24], a[25])), "r"(pack_bf16(a[26], a[27])),
                         "r"(pack_bf16(a[28], a[29])), "r"(pack_bf16(a[30], a[31])) : "memory");
#pragma unroll
            for (int i = 0; i < 12; i++) qb[i] = pack_bf16(a[2 * i], a[2 * i + 1]);
            if (wg == 0) asm volatile("st.shared.v4.b32 [%0], {%1, %2, %3, %4};" ::"r"(qx + 4096), "r"(qb[8]), "r"(qb[9]), "r"(qb[10]), "r"(qb[11]) : "memory");
            else g_q[blockIdx.x * 128 + (tid & 127)] = make_uint4(qb[8], qb[9], qb[10], qb[11]);
            bar_arrive(8, 384);
        } else {
            bar_sync(8, 384);
#pragma unroll
            for (int i = 0; i < 3; i++)
                asm volatile("ld.shared.v4.b32 {%0, %1, %2, %3}, [%4];" : "=r"(qb[4 * i]), "=r"(qb[4 * i + 1]), "=r"(qb[4 * i + 2]), "=r"(qb[4 * i + 3]) : "r"(qx + i * 2048) : "memory");
            fence_async_smem();
        }
        bar_arrive(1, 512);
        if (tid == 0) TS(3);
        int q2 = 0;
#pragma unroll
        for (int i = 0; i < 6; i++) {
            const int j = (i >> 1) * 4 + (i & 1);
            float s = bf_lo(qb[j]) * bf_lo(qb[j]);
            s = fmaf(bf_hi(qb[j]), bf_hi(qb[j]), s);
            s = fmaf(bf_lo(qb[j + 2]), bf_lo(qb[j + 2]), s);
            s = fmaf(bf_hi(qb[j + 2]), bf_hi(qb[j + 2]), s);
            s += __shfl_xor_sync(0xffffffffu, s, 1);
            s += __shfl_xor_sync(0xffffffffu, s, 2);
            q2 = max(q2, __float_as_int(s) & 0x7fffffff);
        }
        mbar_wait(bars + BAR_ST, 0);
        bool slow;
        {
            const int2 st = *(const int2*)(smem + OFF_BAR + STAT_VAL);
            const int k2 = st.x, vm = st.y;
            const float qn2 = __int_as_float(q2) * (Q_SCALE * Q_SCALE), kn2 = __int_as_float(k2), vx = __int_as_float(vm);
            const bool ok = (qn2 * kn2 < 960.f * 960.f) && (qn2 < 1.6e7f) && (kn2 < 1.6e7f) && (vx < 6.0e4f) && (vx > 9.7e-4f);
            slow = __any_sync(0xffffffffu, bar_or(2 + wg, 128, !ok));
        }
        if (wg < 2) {
            if ((tid & 127) == 0) *(volatile int*)(smem + OFF_STAT + 4 * wg) = slow;
            bar_arrive(11 + wg, 256);
        }
        if (tid == 0) TS(4);
        const int nround = wg < 2 ? 3 : 4;
        const uint64_t kd0 = mkdesc(sb + OFF_K, 16, 256, 3), vd0 = mkdesc(sb + OFF_V, OFF_ONES - OFF_V, 256, 3);
#pragma unroll 1
        for (int r = 0; r < nround; r++) {
            const bool last = r >= 2, helper = last && wg == 2;
            const int h = last ? 2 : (wg < 2 ? r : 3), half = wg < 2 ? wg : (r & 1), r0 = half * 64 + wq4 * 16;
            uint8_t* ounit = g_o + (size_t)((rb * 4 + h) * 4 + (c >> 1)) * UNIT;
            if (helper) {
                bar_sync(11 + half, 256);
                slow = __any_sync(0xffffffffu, *(volatile int*)(smem + OFF_STAT + 4 * half));
                if (r == 2) bar_sync(13, 256);
            }
            if (!slow) {
                uint32_t q[4];
#pragma unroll
                for (int i = 0; i < 4; i++) q[i] = pack_f16(bf_lo(qb[i]) * (Q_SCALE / 32.f), bf_hi(qb[i]) * (Q_SCALE / 32.f));
                float O[12];
#pragma unroll
                for (int i = 0; i < 12; i++) O[i] = 0.f;
                pin(O);
                uint32_t mrun = H2C(0xFBFF), cxp = H2C(0x7C00);
                const int t0 = helper ? SPLIT_T : 0, t1 = (last && wg < 2) ? SPLIT_T : 8;
                uint64_t kd = kd0 + t0 * K_INC, vd = vd0 + (uint64_t)(t0 * 16 * V_INC);
#pragma unroll 1
                for (int t = t0; t < t1; t++) {
                    if (r == 0) mbar_wait(bars + BAR_KV + 8 * t, 0);
                    attn_tile(O, q, mrun, cxp, kd, vd, lane);
                    kd += K_INC;
                    vd += (uint64_t)(16 * V_INC);
                }
                if (last) {
                    float* mb = (float*)(smem + OFF_MERGE + half * 5632) + (tid & 127);
                    if (helper) {
#pragma unroll
                        for (int i = 0; i < 9; i++) mb[128 * i] = O[i];
                        mb[128 * 9] = O[10];
                        mb[128 * 10] = __uint_as_float(cxp);
                        bar_arrive(14 + half, 256);
                    } else {
                        bar_sync(14 + half, 256);
                        const uint32_t cxo = __float_as_uint(mb[128 * 10]);
                        const uint32_t cxm = h2min(cxp, cxo), da = h2sub(cxm, cxp), db = h2sub(cxm, cxo);
                        const float a0 = ex2f(h_lo(da)), a1 = ex2f(h_hi(da)), b0 = ex2f(h_lo(db)), b1 = ex2f(h_hi(db));
#pragma unroll
                        for (int i = 0; i < 9; i++) O[i] = fmaf(O[i], (i & 2) ? a1 : a0, mb[128 * i] * ((i & 2) ? b1 : b0));
                        O[10] = fmaf(O[10], a1, mb[128 * 9] * b1);
                    }
                }
                if (!helper) {
                    const float i0 = rcp_fast(O[8]), i1 = rcp_fast(O[10]);
                    const int R = r0 + g;
                    uint8_t* p = ounit + R * 64 + ((((c & 1) * 2 + (t4 >> 1)) ^ ((R >> 1) & 3)) << 4) + (t4 & 1) * 8;
                    *(uint2*)p = make_uint2(pack_bf16(O[0] * i0, O[1] * i0), pack_bf16(O[4] * i0, O[5] * i0));
                    *(uint2*)(p + 512) = make_uint2(pack_bf16(O[2] * i1, O[3] * i1), pack_bf16(O[6] * i1, O[7] * i1));
                }
            } else if (!helper) {
                attn_slow(qb, ounit, r0, (c & 1) * 2, lane);
            }
            __syncwarp();
            if (lane == 0 && !helper) {
                if (h == 2) signal_add(&g_sync[SY_O + (rb * 4 + 2) * 32]);
                else asm volatile("mbarrier.arrive.shared::cta.b64 _, [%0];" ::"r"(bars + BAR_OH + 8 * h) : "memory");
            }
            if (tid == 0) TS(5 + r);
            if (tid == 256) TS(8 + r);
#pragma unroll
            for (int i = 0; i < 8; i++) qb[i] = qb[i + 4];
            if (wg == 2 && r == 0) {
                const uint4 v = __ldcg(&g_q[blockIdx.x * 128 + (tid & 127)]);
                qb[8] = v.x; qb[9] = v.y; qb[10] = v.z; qb[11] = v.w;
            }
        }
    } else {
        const bool prod = warp == 12;
        const bool kvwarp = wq4 == (c & 3);
        bar_arrive(6, 512);
        bar_sync(5, 128);
        if (tid == 384) TS(32);
        {
            float a[16];
#pragma unroll
            for (int i = 0; i < 16; i++) a[i] = 0.f;
            pin(a);
            const uint64_t ad = mkdesc(sb + OFF_XN + (c >> 2) * 65536, 16, 8192, 1), bd = mkdesc(sb + OFF_WK, 16384, 256, 3);
            wg_fence();
#pragma unroll
            for (int k = 0; k < 32; k++) wgmma_ss(a, ad + (k >> 2) * 64 + (k & 3) * 2, bd + k * 32);
            wg_commit();
            if (lane < 4) {
                const int j = wq4 * 4 + lane, q = 2 * c + (j >> 3), kc = j & 7;
                bulk_s2g(g_xn + (size_t)(rb * 8 + kc) * 16384 + q * 1024, sb + OFF_XN + q * 8192 + kc * 1024, 1024);
                bulk_commit();
            }
            __syncwarp();
            wg_wait<0>();
            pin(a);
            bar_arrive(9, 384);
            if (tid == 384) TS(33);
            if (kvwarp) {
                uint32_t w[8];
#pragma unroll
                for (int i = 0; i < 8; i++) w[i] = pack_bf16(a[2 * i], a[2 * i + 1]);
                int k2 = 0, vm = 0;
                uint8_t* stg = smem + OFF_STAT;
                const int key0 = rb * 128 + c * 16;
#pragma unroll
                for (int hh = 0; hh < 2; hh++) {
                    const int kr = g + 8 * hh, sw = (kr >> 2) & 1;
                    float s = 0.f;
#pragma unroll
                    for (int b = 0; b < 2; b++) {
                        const uint32_t kk = w[2 * b + hh], vv = w[4 + 2 * b + hh];
                        *(uint32_t*)(stg + kr * 32 + ((b ^ sw) << 4) + 4 * t4) = pack_f16(bf_lo(kk) * 0.0625f, bf_hi(kk) * 0.0625f);
                        *(uint32_t*)(stg + 512 + kr * 32 + (((t4 & 1) ^ sw) << 4) + 8 * b + 4 * (t4 >> 1)) = pack_f16(bf_lo(vv), bf_hi(vv));
                        s = fmaf(bf_lo(kk), bf_lo(kk), fmaf(bf_hi(kk), bf_hi(kk), s));
                        vm = max(vm, max((int)((vv << 16) & 0x7fffffff), (int)(vv & 0x7fff0000)));
                    }
                    s += __shfl_xor_sync(0xffffffffu, s, 1);
                    s += __shfl_xor_sync(0xffffffffu, s, 2);
                    k2 = max(k2, __float_as_int(s) & 0x7fffffff);
                    g_kvb[(key0 + kr) * 4 + t4] = make_uint4(w[hh], w[2 + hh], w[4 + hh], w[6 + hh]);
                }
                fence_async_smem();
                __syncwarp();
                if (elect()) {
                    bulk_s2g(g_kv + key0 * 32, sb + OFF_STAT, 512);
                    bulk_s2g(g_kv + 65536 + key0 * 32, sb + OFF_STAT + 512, 512);
                    bulk_commit();
                }
#pragma unroll
                for (int m = 4; m < 32; m <<= 1) k2 = imax_xor(k2, m);
#pragma unroll
                for (int m = 1; m < 32; m <<= 1) vm = imax_xor(vm, m);
                if (lane < 2)
                    asm volatile("red.relaxed.gpu.global.max.u64 [%0], %1;" ::"l"(&g_sync[SY_MAX + 2 * lane]),
                                 "l"(((unsigned long long)(epoch + 1) << 32) | (uint32_t)(lane ? vm : k2)) : "memory");
                if (lane == 0) TS(34);
            }
            bulk_wait_all();
            bar_sync(5, 128);
            if (tid == 384) TS(35);
            if (kvwarp && lane == 0) { signal_add(&g_sync[SY_KV]); TS(12); }
            __syncwarp();
        }
        bar_sync(1, 512);
        const uint32_t ring = __shfl_sync(0xffffffffu, sb, 0) + OFF_RING;
        const uint32_t rbar = ring - OFF_RING + OFF_BAR;
        const uint8_t* xn_src = g_xn + (size_t)rb * 131072;
        auto issue1 = [&](int it) {
            const int pass = it / 9, kc = it - 9 * pass, col = 224 * c + (pass ? 32 + 64 * pass : 0);
            const uint32_t slot = ring + (it % 3) * 32768, bar = rbar + BAR_R1 + (it % 3) * 8;
            mbar_expect(bar, pass ? 24576 : 32768);
            bulk_g2s(slot, xn_src + kc * 16384, 16384, bar);
            tma2(slot + 16384, &P.w1, bar, col, kc * 64);
            if (!pass) tma2(slot + 24576, &P.w1, bar, col + 64, kc * 64);
        };
        if (prod) {
            if (lane == 0) TS(13);
            flag_wait(&g_sync[SY_KV], (epoch + 1) * 128);
            if (lane == 0) TS(14);
          if (elect()) {
            uint32_t a0, a1, a2, a3;
            asm volatile("ld.relaxed.gpu.global.v4.u32 {%0, %1, %2, %3}, [%4];" : "=r"(a0), "=r"(a1), "=r"(a2), "=r"(a3) : "l"(&g_sync[SY_MAX]) : "memory");
            fence_async_global();
#pragma unroll
            for (int t = 0; t < 8; t++) {
                const uint32_t bar = bars + BAR_KV + 8 * t;
                mbar_expect(bar, 16384);
                bulk_g2s(sb + OFF_K + t * 8192, g_kv + t * 8192, 8192, bar);
                bulk_g2s(sb + OFF_V + t * 8192, g_kv + 65536 + t * 8192, 8192, bar);
                if (t == 1) {
                    issue1(0);
                    *(uint2*)(smem + OFF_BAR + STAT_VAL) = make_uint2(a0, a2);
                    asm volatile("mbarrier.arrive.shared::cta.b64 _, [%0];" ::"r"(bars + BAR_ST) : "memory");
                    issue1(1);
                    issue1(2);
                }
            }
            if (blockIdx.x == 0) asm volatile("st.relaxed.gpu.global.u32 [%0], %1;" ::"l"(&g_sync[SY_EPOCH]), "r"(epoch + 1) : "memory");
            l2_prefetch(P.w1p + blockIdx.x * 14336, 14336);
            prefetch_map(&P.w2); prefetch_map(&P.wo); prefetch_map(&P.out);
            l2_prefetch(P.w2p + blockIdx.x * 14336, 14336);
            l2_prefetch(P.wop + blockIdx.x * 4096, 4096);
          }
        }
        __syncwarp();
        uint8_t* h_dst = g_h + (size_t)(rb * 56 + 7 * c) * UNIT;
        auto ffn1_pass = [&](auto nu, int pass) {
            constexpr int NU = decltype(nu)::value;
            float c0[NU * 16], c1[NU * 16];
#pragma unroll
            for (int i = 0; i < NU * 16; i++) { c0[i] = 0.f; c1[i] = 0.f; }
            pin(c0); pin(c1);
#pragma unroll 1
            for (int j = 0; j < 8; j++) {
                const int it = 9 * pass + j, s = j % 3;
                mbar_wait(rbar + BAR_R1 + s * 8, (it / 3 - (s == 2 ? pass : 0)) & 1);
                gemm_item<true>(c0, c1, ring + s * 32768, ring + s * 32768 + 16384);
                wg_wait<1>();
                bar_sync(5, 128);
                if (prod && it > 0 && j != 6 && it != 25 && elect()) {
                    if (j == 0) bulk_wait_read();
                    issue1(it + 2);
                }
                __syncwarp();
            }
            wg_wait<0>();
            pin(c0); pin(c1);
            stage_h<NU>(c0, ring + 2 * 32768, wq4 * 16, lane);
            stage_h<NU>(c1, ring + 2 * 32768, 64 + wq4 * 16, lane);
            fence_async_smem();
            bar_sync(5, 128);
            if (prod && elect()) {
                if (pass < 2) issue1(9 * pass + 10);
                bulk_s2g(h_dst + (pass ? 1 + 2 * pass : 0) * UNIT, ring + 2 * 32768, NU * UNIT);
                bulk_commit();
                if (pass == 2) {
                    bulk_wait_all();
                    signal_add(&g_sync[SY_H + rb * 32]);
                }
                TS(pass == 2 ? 16 : 15);
            }
            __syncwarp();
        };
        ffn1_pass(std::integral_constant<int, 3>{}, 0);
#pragma unroll 1
        for (int pass = 1; pass < 3; pass++) ffn1_pass(std::integral_constant<int, 2>{}, pass);
        float c0[32], c1[32];
        {
            const __nv_bfloat16* xp = P.x + (size_t)(rb * 128 + wq4 * 16 + g) * DM + c * 64 + 2 * t4;
#pragma unroll
            for (int j = 0; j < 8; j++) {
                const uint32_t v0 = ldg_here(xp + 8 * j), v1 = ldg_here(xp + 8 * DM + 8 * j);
                const uint32_t v2 = ldg_here(xp + 64 * DM + 8 * j), v3 = ldg_here(xp + 72 * DM + 8 * j);
                c0[4 * j] = bf_lo(v0); c0[4 * j + 1] = bf_hi(v0); c0[4 * j + 2] = bf_lo(v1); c0[4 * j + 3] = bf_hi(v1);
                c1[4 * j] = bf_lo(v2); c1[4 * j + 1] = bf_hi(v2); c1[4 * j + 2] = bf_lo(v3); c1[4 * j + 3] = bf_hi(v3);
            }
            pin(c0); pin(c1);
        }
        const uint8_t* h_src = g_h + (size_t)rb * 56 * UNIT;
        const uint8_t* o_src = g_o + (size_t)rb * 16 * UNIT;
        auto head_of = [](int it) { const int p = (it - 28) >> 1; return p < 2 ? p : 5 - p; };
        auto issue2 = [&](int it) {
            const uint32_t slot = ring + (it < 28 ? it & 3 : (it - 28) % 3) * 24576;
            const uint32_t bar = it < 28 ? rbar + BAR_R2 + (it & 3) * 8 : rbar + BAR_O + (it - 28) * 8;
            mbar_expect(bar, 24576);
            if (it < 28) {
                tma2(slot + 16384, &P.w2, bar, 64 * c, it * 64);
                bulk_g2s(slot, h_src + it * 16384, 16384, bar);
            } else {
                const int h = head_of(it);
                tma3(slot + 16384, &P.wo, bar, 64 * c, 16 * h, 4 * (it & 1));
                bulk_g2s(slot, o_src + (h * 4 + 2 * (it & 1)) * UNIT, 16384, bar);
            }
        };
        if (prod) {
            flag_wait(&g_sync[SY_H + rb * 32], (epoch + 1) * 8);
            if (lane == 0) TS(17);
            if (elect()) {
                fence_async_global();
#pragma unroll 1
                for (int i = 0; i < 4; i++) issue2(i);
            }
            __syncwarp();
        }
        bar_sync(5, 128);
#pragma unroll 1
        for (int it = 0; it < 28; it++) {
            mbar_wait(rbar + BAR_R2 + (it & 3) * 8, (it >> 2) & 1);
            gemm_item<false>(c0, c1, ring + (it & 3) * 24576, ring + (it & 3) * 24576 + 16384);
            wg_wait<1>();
            bar_sync(5, 128);
            if (prod && it >= 1 && it < 25 && elect()) issue2(it + 3);
            __syncwarp();
        }
        wg_wait<0>();
        pin(c0); pin(c1);
        bar_arrive(13, 256);
        bar_sync(5, 128);
#pragma unroll 1
        for (int seg = 0; seg < 3; seg++) {
            const int first = seg == 0 ? 28 : 26 + 4 * seg, n = seg == 1 ? 4 : 2;
            if (prod) {
                uint32_t* f = &g_sync[SY_O + (rb * 4 + seg) * 32];
                if (seg < 2) {
                    mbar_wait(bars + BAR_OH + 8 * seg, 0);
                    if (seg == 1) mbar_wait(bars + BAR_OH + 24, 0);
                    if (elect()) {
                        signal_add(f);
                        if (seg == 1) asm volatile("red.relaxed.gpu.global.add.u32 [%0], 1;" ::"l"(f + 64) : "memory");
                    }
                    __syncwarp();
                }
                if (seg == 1) flag_wait(f + 64, (epoch + 1) * 8);
                flag_wait(f, (epoch + 1) * (seg == 2 ? 64 : 8));
                if (lane == 0) TS(18 + seg);
                if (elect()) {
                    fence_async_global();
#pragma unroll 1
                    for (int i = first; i < first + (n > 3 ? 3 : n); i++) issue2(i);
                }
                __syncwarp();
            }
            bar_sync(5, 128);
#pragma unroll 1
            for (int it = first; it < first + n; it++) {
                const uint32_t slot = ring + ((it - 28) % 3) * 24576;
                mbar_wait(rbar + BAR_O + (it - 28) * 8, 0);
                gemm_item<false>(c0, c1, slot, slot + 16384);
                if (it == 31) {
                    wg_wait<1>();
                    bar_sync(5, 128);
                    if (prod && elect()) issue2(33);
                    __syncwarp();
                }
            }
            wg_wait<0>();
            pin(c0); pin(c1);
            bar_sync(5, 128);
        }
        if (tid == 384) TS(22);
        bar_sync(5, 128);
        {
            const int row = wq4 * 16 + ((lane >> 3) & 1) * 8 + (lane & 7);
#pragma unroll
            for (int j = 0; j < 8; j += 2) {
                const uint32_t a = ring + row * 128 + (((j + (lane >> 4)) ^ (row & 7)) << 4);
                stsm4(a, pack_bf16(c0[4 * j], c0[4 * j + 1]), pack_bf16(c0[4 * j + 2], c0[4 * j + 3]),
                      pack_bf16(c0[4 * j + 4], c0[4 * j + 5]), pack_bf16(c0[4 * j + 6], c0[4 * j + 7]));
                stsm4(a + 8192, pack_bf16(c1[4 * j], c1[4 * j + 1]), pack_bf16(c1[4 * j + 2], c1[4 * j + 3]),
                      pack_bf16(c1[4 * j + 4], c1[4 * j + 5]), pack_bf16(c1[4 * j + 6], c1[4 * j + 7]));
            }
            fence_async_smem();
            bar_sync(5, 128);
            if (prod && elect()) {
                tma2_store(&P.out, ring, c * 64, rb * 128);
                bulk_commit();
                bulk_wait_read();
                TS(23); TSG(61);
            }
        }
    }
}

typedef CUresult (*EncodeFn)(CUtensorMap*, CUtensorMapDataType, cuuint32_t, void*, const cuuint64_t*, const cuuint64_t*, const cuuint32_t*,
                             const cuuint32_t*, CUtensorMapInterleave, CUtensorMapSwizzle, CUtensorMapL2promotion, CUtensorMapFloatOOBfill);

void encode(EncodeFn fn, CUtensorMap* m, const void* p, int rank, const cuuint64_t* dims, const cuuint64_t* strides, const cuuint32_t* box, CUtensorMapSwizzle sw) {
    const cuuint32_t es[5] = {1, 1, 1, 1, 1};
    fn(m, CU_TENSOR_MAP_DATA_TYPE_BFLOAT16, rank, const_cast<void*>(p), dims, strides, box, es, CU_TENSOR_MAP_INTERLEAVE_NONE, sw,
       CU_TENSOR_MAP_L2_PROMOTION_L2_256B, CU_TENSOR_MAP_FLOAT_OOB_FILL_NONE);
}

}

extern "C" void kernel_launch(void* const* d_in, const int* in_sizes, int n_in, void* d_out, int out_size) {
    (void)in_sizes; (void)n_in; (void)out_size;
    static EncodeFn fn = nullptr;
    if (!fn) {
        void* p = nullptr;
        cudaDriverEntryPointQueryResult qr;
        cudaGetDriverEntryPoint("cuTensorMapEncodeTiled", &p, cudaEnableDefault, &qr);
        fn = (EncodeFn)p;
        cudaFuncSetAttribute(fused_mqa_ffn_kernel, cudaFuncAttributeMaxDynamicSharedMemorySize, SMEM_BYTES);
    }
    Params P;
    {
        const cuuint64_t d[2] = {DM, DM}, s[1] = {DM * 2};
        const cuuint32_t b[2] = {64, 256};
        encode(fn, &P.wq, d_in[1], 2, d, s, b, CU_TENSOR_MAP_SWIZZLE_128B);
    }
    {
        const cuuint64_t d[2] = {DFF, DM}, s[1] = {DFF * 2};
        const cuuint32_t b[2] = {64, 64};
        encode(fn, &P.w1, d_in[6], 2, d, s, b, CU_TENSOR_MAP_SWIZZLE_128B);
    }
    {
        const cuuint64_t d[2] = {DM, DFF}, s[1] = {DM * 2};
        const cuuint32_t b[2] = {64, 64};
        encode(fn, &P.w2, d_in[7], 2, d, s, b, CU_TENSOR_MAP_SWIZZLE_128B);
    }
    {
        const cuuint64_t d[3] = {DM, 64, 8}, s[2] = {DM * 2, 64 * DM * 2};
        const cuuint32_t b[3] = {64, 16, 4};
        encode(fn, &P.wo, d_in[4], 3, d, s, b, CU_TENSOR_MAP_SWIZZLE_128B);
    }
    {
        const cuuint64_t d[2] = {DM, SEQ}, s[1] = {DM * 2};
        const cuuint32_t b[2] = {64, 128};
        encode(fn, &P.out, d_out, 2, d, s, b, CU_TENSOR_MAP_SWIZZLE_128B);
    }
    P.x = (const __nv_bfloat16*)d_in[0];
    P.wkp = (const uint8_t*)d_in[2];
    P.wvp = (const uint8_t*)d_in[3];
    P.w1p = (const uint8_t*)d_in[6];
    P.w2p = (const uint8_t*)d_in[7];
    P.wop = (const uint8_t*)d_in[4];
    fused_mqa_ffn_kernel<<<128, 512, SMEM_BYTES, cudaStreamPerThread>>>(P);
}
```

```cpp
#include <cuda_runtime.h>
#include <cuda.h>
#include <cuda_bf16.h>
#include <cuda_fp16.h>
#include <stdint.h>
#include <utility>

namespace {

constexpr int SEQ = 2048, DM = 512, DFF = 1792;
#define POLY_MASK 0x66666666u
#define LN_PRIO 2
#define SPLIT_T 5
#define FOLD_LATE 0
#define TUNROLL 1
#define PVCH 1

constexpr int TUNROLL_C = TUNROLL;
constexpr int UNIT = 8192;
__device__ __align__(1024) uint8_t g_kv[131072];
__device__ __align__(1024) uint4   g_kvb[SEQ * 4];
__device__ __align__(1024) uint8_t g_xn[16 * 8 * 16384];
__device__ __align__(1024) uint8_t g_h[16 * 56 * UNIT];
__device__ __align__(1024) uint4   g_q[128 * 8 * 128];
__device__ __align__(1024) uint8_t g_o[16 * 16 * UNIT];
__device__ __align__(1024) uint32_t g_sync[32 * (2 + 16 + 64)];
constexpr int SY_EPOCH = 0, SY_KV = 1, SY_MAX = 4, SY_H = 64, SY_O = 64 + 16 * 32;
#define TS(i) do {} while (0)
#define TSG(i) do {} while (0)

constexpr uint32_t OFF_XN = 0;
constexpr uint32_t OFF_K = 0, OFF_V = 65536;
constexpr uint32_t OFF_ONES = 131072;
constexpr uint32_t OFF_RING = 132096;
constexpr uint32_t OFF_WQ = OFF_RING, OFF_WK = OFF_RING + 65536, OFF_WV = OFF_RING + 81920;
constexpr uint32_t OFF_MERGE = OFF_RING + 73728;
constexpr uint32_t OFF_STAT = OFF_RING + 98304;
constexpr uint32_t OFF_BAR = OFF_STAT + 1024;
constexpr uint32_t SMEM_BYTES = OFF_BAR + 768;
constexpr uint32_t BAR_WQ = 0, BAR_WKV = 8, BAR_KV = 16, BAR_R1 = 80, BAR_R2 = 104, BAR_X = 136, BAR_ST = 264, STAT_VAL = 272, BAR_OH = 280, BAR_O = 312;
constexpr int N_BARS = 17;

template <class F, int... I> __device__ __forceinline__ void static_for_impl(F&& f, std::integer_sequence<int, I...>) { (f(std::integral_constant<int, I>{}), ...); }
template <int N, class F> __device__ __forceinline__ void static_for(F&& f) { static_for_impl(f, std::make_integer_sequence<int, N>{}); }

__device__ __forceinline__ void wg_fence() { asm volatile("wgmma.fence.sync.aligned;" ::: "memory"); }
__device__ __forceinline__ void wg_commit() { asm volatile("wgmma.commit_group.sync.aligned;" ::: "memory"); }
template <int N> __device__ __forceinline__ void wg_wait() { asm volatile("wgmma.wait_group.sync.aligned %0;" ::"n"(N) : "memory"); }
__device__ __forceinline__ void pin(float& x) { asm volatile("" : "+f"(x)::"memory"); }
__device__ __forceinline__ void pin(uint32_t& x) { asm volatile("" : "+r"(x)::"memory"); }
template <class T, int N> __device__ __forceinline__ void pin(T (&d)[N]) {
#pragma unroll
    for (int i = 0; i < N; i++) pin(d[i]);
}
__device__ __forceinline__ uint64_t mkdesc(uint32_t addr, uint32_t lbo, uint32_t sbo, uint32_t sw) {
    return (uint64_t)((addr >> 4) | ((lbo >> 4) << 16)) | ((uint64_t)((sbo >> 4) | (sw << 30)) << 32);
}
__device__ __forceinline__ void mbar_init(uint32_t bar, int cnt) { asm volatile("mbarrier.init.shared::cta.b64 [%0], %1;" ::"r"(bar), "r"(cnt) : "memory"); }
__device__ __forceinline__ void mbar_expect(uint32_t bar, uint32_t bytes) { asm volatile("mbarrier.arrive.expect_tx.shared::cta.b64 _, [%0], %1;" ::"r"(bar), "r"(bytes) : "memory"); }
__device__ __forceinline__ bool mbar_try(uint32_t bar, uint32_t par) {
    uint32_t r;
    asm volatile("{.reg .pred p; mbarrier.try_wait.parity.shared::cta.b64 p, [%1], %2, %3; selp.u32 %0, 1, 0, p;}" : "=r"(r) : "r"(bar), "r"(par), "r"(20000u) : "memory");
    return r;
}
__device__ __forceinline__ void mbar_wait(uint32_t bar, uint32_t par) {
    int n = 0;
    while (!__all_sync(0xffffffffu, mbar_try(bar, par) | (++n > (1 << 16)))) {}
}
__device__ __forceinline__ bool elect() {
    uint32_t r;
    asm volatile("{.reg .pred p; elect.sync _|p, 0xffffffff; selp.u32 %0, 1, 0, p;}" : "=r"(r));
    return r;
}
__device__ __forceinline__ void bulk_g2s(uint32_t dst, const void* src, uint32_t bytes, uint32_t bar) {
    asm volatile("cp.async.bulk.shared::cluster.global.mbarrier::complete_tx::bytes [%0], [%1], %2, [%3];" ::"r"(dst), "l"(src), "r"(bytes), "r"(bar) : "memory");
}
__device__ __forceinline__ void bulk_s2g(void* dst, uint32_t src, uint32_t bytes) {
    asm volatile("cp.async.bulk.global.shared::cta.bulk_group [%0], [%1], %2;" ::"l"(dst), "r"(src), "r"(bytes) : "memory");
}
__device__ __forceinline__ void bulk_commit() { asm volatile("cp.async.bulk.commit_group;" ::: "memory"); }
__device__ __forceinline__ void bulk_wait_all() { asm volatile("cp.async.bulk.wait_group 0;" ::: "memory"); }
__device__ __forceinline__ void bulk_wait_read() { asm volatile("cp.async.bulk.wait_group.read 0;" ::: "memory"); }
__device__ __forceinline__ void l2_prefetch(const void* p, uint32_t bytes) { asm volatile("cp.async.bulk.prefetch.L2.global [%0], %1;" ::"l"(p), "r"(bytes) : "memory"); }
__device__ __forceinline__ void tma2(uint32_t dst, const CUtensorMap* m, uint32_t bar, int c0, int c1) {
    asm volatile("cp.async.bulk.tensor.2d.shared::cluster.global.mbarrier::complete_tx::bytes [%0], [%1, {%3, %4}], [%2];" ::"r"(dst), "l"(m), "r"(bar), "r"(c0), "r"(c1) : "memory");
}
__device__ __forceinline__ void tma3(uint32_t dst, const CUtensorMap* m, uint32_t bar, int c0, int c1, int c2) {
    asm volatile("cp.async.bulk.tensor.3d.shared::cluster.global.mbarrier::complete_tx::bytes [%0], [%1, {%3, %4, %5}], [%2];" ::"r"(dst), "l"(m), "r"(bar), "r"(c0), "r"(c1), "r"(c2) : "memory");
}
__device__ __forceinline__ void tma2_store(const CUtensorMap* m, uint32_t src, int c0, int c1) {
    asm volatile("cp.async.bulk.tensor.2d.global.shared::cta.bulk_group [%0, {%2, %3}], [%1];" ::"l"(m), "r"(src), "r"(c0), "r"(c1) : "memory");
}
__device__ __forceinline__ void prefetch_map(const CUtensorMap* m) { asm volatile("prefetch.tensormap [%0];" ::"l"(m) : "memory"); }
__device__ __forceinline__ void fence_async_smem() { asm volatile("fence.proxy.async.shared::cta;" ::: "memory"); }
__device__ __forceinline__ void fence_async_global() { asm volatile("fence.proxy.async.global;" ::: "memory"); }
__device__ __forceinline__ void bar_sync(int id, int n) { asm volatile("bar.sync %0, %1;" ::"r"(id), "r"(n) : "memory"); }
__device__ __forceinline__ void bar_arrive(int id, int n) { asm volatile("bar.arrive %0, %1;" ::"r"(id), "r"(n) : "memory"); }
__device__ __forceinline__ bool bar_or(int id, int n, bool p) {
    uint32_t r;
    asm volatile("{.reg .pred a, b; setp.ne.u32 a, %3, 0; bar.red.or.pred b, %1, %2, a; selp.u32 %0, 1, 0, b;}" : "=r"(r) : "r"(id), "r"(n), "r"((uint32_t)p) : "memory");
    return r;
}
__device__ __forceinline__ void signal_add(uint32_t* p) {
    asm volatile("red.release.gpu.global.add.u32 [%0], 1;" ::"l"(p) : "memory");
}
__device__ __forceinline__ void flag_wait(const uint32_t* p, uint32_t target) {
    int n = 0;
    uint32_t v;
    do {
        asm volatile("ld.relaxed.gpu.global.u32 %0, [%1];" : "=r"(v) : "l"(p) : "memory");
    } while (!__all_sync(0xffffffffu, ((int)(v - target) >= 0) | (++n > (1 << 21))));
    asm volatile("fence.acquire.gpu;" ::: "memory");
}
__device__ __forceinline__ void stsm4(uint32_t addr, uint32_t r0, uint32_t r1, uint32_t r2, uint32_t r3) {
    asm volatile("stmatrix.sync.aligned.m8n8.x4.shared.b16 [%0], {%1, %2, %3, %4};" ::"r"(addr), "r"(r0), "r"(r1), "r"(r2), "r"(r3) : "memory");
}
__device__ __forceinline__ uint32_t pack_bf16(float lo, float hi) { uint32_t d; asm("cvt.rn.bf16x2.f32 %0, %1, %2;" : "=r"(d) : "f"(hi), "f"(lo)); return d; }
__device__ __forceinline__ uint32_t pack_bf16_relu(float lo, float hi) { uint32_t d; asm("cvt.rn.relu.bf16x2.f32 %0, %1, %2;" : "=r"(d) : "f"(hi), "f"(lo)); return d; }
__device__ __forceinline__ uint32_t pack_f16(float lo, float hi) { uint32_t d; asm("cvt.rn.f16x2.f32 %0, %1, %2;" : "=r"(d) : "f"(hi), "f"(lo)); return d; }
__device__ __forceinline__ float bf_lo(uint32_t v) { return __uint_as_float(v << 16); }
__device__ __forceinline__ float bf_hi(uint32_t v) { return __uint_as_float(v & 0xffff0000u); }
__device__ __forceinline__ float bf_round(float x) { return bf_lo(pack_bf16(x, 0.f)); }
__device__ __forceinline__ uint32_t bf2fma(uint32_t a, uint32_t b, uint32_t c) { uint32_t d; asm("fma.rn.bf16x2 %0, %1, %2, %3;" : "=r"(d) : "r"(a), "r"(b), "r"(c)); return d; }
__device__ __forceinline__ uint32_t h2fma(uint32_t a, uint32_t b, uint32_t c) { uint32_t d; asm("fma.rn.f16x2 %0, %1, %2, %3;" : "=r"(d) : "r"(a), "r"(b), "r"(c)); return d; }
__device__ __forceinline__ uint32_t h2fma_sat(uint32_t a, uint32_t b, uint32_t c) { uint32_t d; asm("fma.rn.sat.f16x2 %0, %1, %2, %3;" : "=r"(d) : "r"(a), "r"(b), "r"(c)); return d; }
__device__ __forceinline__ uint32_t h2sub(uint32_t a, uint32_t b) { uint32_t d; asm("sub.f16x2 %0, %1, %2;" : "=r"(d) : "r"(a), "r"(b)); return d; }
__device__ __forceinline__ uint32_t h2mul(uint32_t a, uint32_t b) { uint32_t d; asm("mul.f16x2 %0, %1, %2;" : "=r"(d) : "r"(a), "r"(b)); return d; }
__device__ __forceinline__ uint32_t h2max(uint32_t a, uint32_t b) { uint32_t d; asm("max.f16x2 %0, %1, %2;" : "=r"(d) : "r"(a), "r"(b)); return d; }
__device__ __forceinline__ uint32_t h2min(uint32_t a, uint32_t b) { uint32_t d; asm("min.f16x2 %0, %1, %2;" : "=r"(d) : "r"(a), "r"(b)); return d; }
__device__ __forceinline__ uint32_t h2ex2(uint32_t a) { uint32_t d; asm("ex2.approx.f16x2 %0, %1;" : "=r"(d) : "r"(a)); return d; }
__device__ __forceinline__ uint32_t prmt(uint32_t a, uint32_t b, uint32_t s) { uint32_t d; asm("prmt.b32 %0, %1, %2, %3;" : "=r"(d) : "r"(a), "r"(b), "r"(s)); return d; }
__device__ __forceinline__ float ex2f(float a) { float d; asm("ex2.approx.ftz.f32 %0, %1;" : "=f"(d) : "f"(a)); return d; }
__device__ __forceinline__ float sqrt_fast(float a) { float d; asm("sqrt.approx.f32 %0, %1;" : "=f"(d) : "f"(a)); return d; }
__device__ __forceinline__ float rcp_fast(float a) { float d; asm("rcp.approx.f32 %0, %1;" : "=f"(d) : "f"(a)); return d; }
__device__ __forceinline__ float h_lo(uint32_t a) { float d; asm("{.reg .b16 l, h; mov.b32 {l, h}, %1; cvt.f32.f16 %0, l;}" : "=f"(d) : "r"(a)); return d; }
__device__ __forceinline__ float h_hi(uint32_t a) { float d; asm("{.reg .b16 l, h; mov.b32 {l, h}, %1; cvt.f32.f16 %0, h;}" : "=f"(d) : "r"(a)); return d; }
__device__ __forceinline__ uint32_t bc_lo(uint32_t a) { uint32_t d; asm("{.reg .b16 l, h; mov.b32 {l, h}, %1; mov.b32 %0, {l, l};}" : "=r"(d) : "r"(a)); return d; }
__device__ __forceinline__ uint32_t bc_hi(uint32_t a) { uint32_t d; asm("{.reg .b16 l, h; mov.b32 {l, h}, %1; mov.b32 %0, {h, h};}" : "=r"(d) : "r"(a)); return d; }
__device__ __forceinline__ uint32_t ldg_here(const void* p) { uint32_t v; asm volatile("ld.global.nc.u32 %0, [%1];" : "=r"(v) : "l"(p) : "memory"); return v; }

__device__ __forceinline__ void wgmma_qk(uint32_t (&d)[64], const uint32_t (&a)[4], uint64_t bdesc) {
    asm volatile("wgmma.mma_async.sync.aligned.m64n256k16.f16.f16.f16 {"
        "%0, %1, %2, %3, %4, %5, %6, %7, %8, %9, %10, %11, %12, %13, %14, %15, "
        "%16, %17, %18, %19, %20, %21, %22, %23, %24, %25, %26, %27, %28, %29, %30, %31, "
        "%32, %33, %34, %35, %36, %37, %38, %39, %40, %41, %42, %43, %44, %45, %46, %47, "
        "%48, %49, %50, %51, %52, %53, %54, %55, %56, %57, %58, %59, %60, %61, %62, %63"
        "}, {%64, %65, %66, %67}, %68, 0, 1, 1, 0;\n"
        : "=r"(d[0]), "=r"(d[1]), "=r"(d[2]), "=r"(d[3]), "=r"(d[4]), "=r"(d[5]), "=r"(d[6]), "=r"(d[7]),
          "=r"(d[8]), "=r"(d[9]), "=r"(d[10]), "=r"(d[11]), "=r"(d[12]), "=r"(d[13]), "=r"(d[14]), "=r"(d[15]),
          "=r"(d[16]), "=r"(d[17]), "=r"(d[18]), "=r"(d[19]), "=r"(d[20]), "=r"(d[21]), "=r"(d[22]), "=r"(d[23]),
          "=r"(d[24]), "=r"(d[25]), "=r"(d[26]), "=r"(d[27]), "=r"(d[28]), "=r"(d[29]), "=r"(d[30]), "=r"(d[31]),
          "=r"(d[32]), "=r"(d[33]), "=r"(d[34]), "=r"(d[35]), "=r"(d[36]), "=r"(d[37]), "=r"(d[38]), "=r"(d[39]),
          "=r"(d[40]), "=r"(d[41]), "=r"(d[42]), "=r"(d[43]), "=r"(d[44]), "=r"(d[45]), "=r"(d[46]), "=r"(d[47]),
          "=r"(d[48]), "=r"(d[49]), "=r"(d[50]), "=r"(d[51]), "=r"(d[52]), "=r"(d[53]), "=r"(d[54]), "=r"(d[55]),
          "=r"(d[56]), "=r"(d[57]), "=r"(d[58]), "=r"(d[59]), "=r"(d[60]), "=r"(d[61]), "=r"(d[62]), "=r"(d[63])
        : "r"(a[0]), "r"(a[1]), "r"(a[2]), "r"(a[3]), "l"(bdesc));
}
__device__ __forceinline__ void wgmma_pv0(uint32_t (&d)[6], uint32_t a0, uint32_t a1, uint32_t a2, uint32_t a3, uint64_t bdesc) {
    asm volatile("wgmma.mma_async.sync.aligned.m64n24k16.f16.f16.f16 {%0, %1, %2, %3, %4, %5}, {%6, %7, %8, %9}, %10, 0, 1, 1, 1;\n"
        : "=r"(d[0]), "=r"(d[1]), "=r"(d[2]), "=r"(d[3]), "=r"(d[4]), "=r"(d[5])
        : "r"(a0), "r"(a1), "r"(a2), "r"(a3), "l"(bdesc));
}
__device__ __forceinline__ void wgmma_pv(uint32_t (&d)[6], uint32_t a0, uint32_t a1, uint32_t a2, uint32_t a3, uint64_t bdesc) {
    asm volatile("wgmma.mma_async.sync.aligned.m64n24k16.f16.f16.f16 {%0, %1, %2, %3, %4, %5}, {%6, %7, %8, %9}, %10, 1, 1, 1, 1;\n"
        : "+r"(d[0]), "+r"(d[1]), "+r"(d[2]), "+r"(d[3]), "+r"(d[4]), "+r"(d[5])
        : "r"(a0), "r"(a1), "r"(a2), "r"(a3), "l"(bdesc));
}
__device__ __forceinline__ void wgmma_ss(float (&d)[16], uint64_t adesc, uint64_t bdesc) {
    asm volatile("wgmma.mma_async.sync.aligned.m64n32k16.f32.bf16.bf16 {"
        "%0, %1, %2, %3, %4, %5, %6, %7, %8, %9, %10, %11, %12, %13, %14, %15"
        "}, %16, %17, 1, 1, 1, 0, 1;\n"
        : "+f"(d[0]), "+f"(d[1]), "+f"(d[2]), "+f"(d[3]), "+f"(d[4]), "+f"(d[5]), "+f"(d[6]), "+f"(d[7]),
          "+f"(d[8]), "+f"(d[9]), "+f"(d[10]), "+f"(d[11]), "+f"(d[12]), "+f"(d[13]), "+f"(d[14]), "+f"(d[15])
        : "l"(adesc), "l"(bdesc));
}
__device__ __forceinline__ void wgmma_ss(float (&d)[32], uint64_t adesc, uint64_t bdesc) {
    asm volatile("wgmma.mma_async.sync.aligned.m64n64k16.f32.bf16.bf16 {"
        "%0, %1, %2, %3, %4, %5, %6, %7, %8, %9, %10, %11, %12, %13, %14, %15, "
        "%16, %17, %18, %19, %20, %21, %22, %23, %24, %25, %26, %27, %28, %29, %30, %31"
        "}, %32, %33, 1, 1, 1, 0, 1;\n"
        : "+f"(d[0]), "+f"(d[1]), "+f"(d[2]), "+f"(d[3]), "+f"(d[4]), "+f"(d[5]), "+f"(d[6]), "+f"(d[7]),
          "+f"(d[8]), "+f"(d[9]), "+f"(d[10]), "+f"(d[11]), "+f"(d[12]), "+f"(d[13]), "+f"(d[14]), "+f"(d[15]),
          "+f"(d[16]), "+f"(d[17]), "+f"(d[18]), "+f"(d[19]), "+f"(d[20]), "+f"(d[21]), "+f"(d[22]), "+f"(d[23]),
          "+f"(d[24]), "+f"(d[25]), "+f"(d[26]), "+f"(d[27]), "+f"(d[28]), "+f"(d[29]), "+f"(d[30]), "+f"(d[31])
        : "l"(adesc), "l"(bdesc));
}
__device__ __forceinline__ void wgmma_ss(float (&d)[48], uint64_t adesc, uint64_t bdesc) {
    asm volatile("wgmma.mma_async.sync.aligned.m64n96k16.f32.bf16.bf16 {"
        "%0, %1, %2, %3, %4, %5, %6, %7, %8, %9, %10, %11, %12, %13, %14, %15, "
        "%16, %17, %18, %19, %20, %21, %22, %23, %24, %25, %26, %27, %28, %29, %30, %31, "
        "%32, %33, %34, %35, %36, %37, %38, %39, %40, %41, %42, %43, %44, %45, %46, %47"
        "}, %48, %49, 1, 1, 1, 0, 1;\n"
        : "+f"(d[0]), "+f"(d[1]), "+f"(d[2]), "+f"(d[3]), "+f"(d[4]), "+f"(d[5]), "+f"(d[6]), "+f"(d[7]),
          "+f"(d[8]), "+f"(d[9]), "+f"(d[10]), "+f"(d[11]), "+f"(d[12]), "+f"(d[13]), "+f"(d[14]), "+f"(d[15]),
          "+f"(d[16]), "+f"(d[17]), "+f"(d[18]), "+f"(d[19]), "+f"(d[20]), "+f"(d[21]), "+f"(d[22]), "+f"(d[23]),
          "+f"(d[24]), "+f"(d[25]), "+f"(d[26]), "+f"(d[27]), "+f"(d[28]), "+f"(d[29]), "+f"(d[30]), "+f"(d[31]),
          "+f"(d[32]), "+f"(d[33]), "+f"(d[34]), "+f"(d[35]), "+f"(d[36]), "+f"(d[37]), "+f"(d[38]), "+f"(d[39]),
          "+f"(d[40]), "+f"(d[41]), "+f"(d[42]), "+f"(d[43]), "+f"(d[44]), "+f"(d[45]), "+f"(d[46]), "+f"(d[47])
        : "l"(adesc), "l"(bdesc));
}

#define H2C(x) ((uint32_t)(x) * 0x00010001u)
constexpr uint32_t C_2M15 = H2C(0x0200), C_N2M15 = H2C(0x8200), C_2P15 = H2C(0x7800), C_N2P15 = H2C(0xF800);
constexpr uint32_t C_512 = H2C(0x6000), C_N512 = H2C(0xE000), C_N13P5 = H2C(0xCAC0);
constexpr uint32_t PC0 = H2C(0x05a8), PC1 = H2C(0x27d9), PC2 = H2C(0x4581), PC3 = H2C(0x60ea);
constexpr float Q_SCALE = 0.25f * 1.4426950408889634f;

__device__ __forceinline__ uint32_t exp_mufu(uint32_t s, uint32_t cx) { return h2ex2(h2fma(s, C_512, cx)); }
__device__ __forceinline__ uint32_t exp_fma(uint32_t s, uint32_t cr, uint32_t ct, uint32_t z) {
    const uint32_t r = h2fma_sat(s, C_2M15, cr);
    const uint32_t t = h2fma(r, C_2P15, ct);
    const uint32_t f = h2sub(s, t);
    uint32_t p = h2fma(f, PC3, PC2);
    p = h2fma(p, f, PC1);
    p = h2fma_sat(p, f, PC0);
    uint32_t e;
    asm("shf.l.wrap.b32 %0, %1, %2, 10;" : "=r"(e) : "r"(z), "r"(r));
    return e + p;
}
__host__ __device__ constexpr bool is_poly(int i) { return (POLY_MASK >> (i & 31)) & 1; }

constexpr long long K_INC = 512;
constexpr long long V_INC = 32 - (32 << 16);

__device__ __forceinline__ void attn_fold(float (&O)[10], const uint32_t (&T)[6], float a0, float a1) {
#pragma unroll
    for (int i = 0; i < 4; i++) {
        O[2 * i] = fmaf(O[2 * i], (i & 1) ? a1 : a0, h_lo(T[i]));
        O[2 * i + 1] = fmaf(O[2 * i + 1], (i & 1) ? a1 : a0, h_hi(T[i]));
    }
    O[8] = fmaf(O[8], a0, h_lo(T[4]));
    O[9] = fmaf(O[9], a1, h_lo(T[5]));
}
__device__ __forceinline__ void attn_tile(float (&O)[10], uint32_t (&T)[6], float& a0, float& a1, const uint32_t (&q)[4], uint32_t& mrun, uint32_t& cxp, uint64_t kd, uint64_t vd, uint32_t coff, uint32_t z) {
    uint32_t S[64];
    wg_fence();
    wgmma_qk(S, q, kd);
    wg_commit();
    wg_wait<0>();
    pin(S);
    uint32_t ma = h2max(S[0], S[2]), mb = h2max(S[1], S[3]), mc = h2max(S[4], S[6]), md = h2max(S[5], S[7]);
#pragma unroll
    for (int i = 8; i < 64; i += 8) {
        ma = h2max(h2max(ma, S[i]), S[i + 2]);
        mb = h2max(h2max(mb, S[i + 1]), S[i + 3]);
        mc = h2max(h2max(mc, S[i + 4]), S[i + 6]);
        md = h2max(h2max(md, S[i + 5]), S[i + 7]);
    }
    uint32_t m = h2max(h2max(prmt(ma, mb, 0x5410), prmt(ma, mb, 0x7632)), h2max(prmt(mc, md, 0x5410), prmt(mc, md, 0x7632)));
    m = h2max(m, __shfl_xor_sync(0xffffffffu, m, 1));
    m = h2max(h2max(m, mrun), __shfl_xor_sync(0xffffffffu, m, 2));
    mrun = m;
    const uint32_t cr = h2fma(m, C_N2M15, coff);
    const uint32_t ct = h2mul(cr, C_N2P15);
    const uint32_t cx = h2fma(ct, C_N512, C_N13P5);
    const uint32_t dd = h2sub(cx, cxp);
    cxp = cx;
    a0 = ex2f(h_lo(dd));
    a1 = ex2f(h_hi(dd));
    const uint32_t crA = bc_lo(cr), crB = bc_hi(cr), ctA = bc_lo(ct), ctB = bc_hi(ct), cxA = bc_lo(cx), cxB = bc_hi(cx);
    static_for<16 / PVCH>([&](auto c) {
        constexpr int C = decltype(c)::value;
#pragma unroll
        for (int i = 4 * PVCH * C; i < 4 * PVCH * (C + 1); i++) {
            if (is_poly(i)) S[i] = exp_fma(S[i], (i & 1) ? crB : crA, (i & 1) ? ctB : ctA, z);
            else            S[i] = exp_mufu(S[i], (i & 1) ? cxB : cxA);
        }
        wg_fence();
#pragma unroll
        for (int k = PVCH * C; k < PVCH * (C + 1); k++) {
            if (k == 0) wgmma_pv0(T, S[0], S[1], S[2], S[3], vd);
            else wgmma_pv(T, S[4 * k], S[4 * k + 1], S[4 * k + 2], S[4 * k + 3], vd + k * V_INC);
        }
    });
    wg_commit();
    wg_wait<0>();
    pin(T);
    attn_fold(O, T, a0, a1);
}

__device__ __forceinline__ void attn_slow(const uint32_t (&qb)[4], uint8_t* ounit, int r0, int chunk0, int lane) {
    const int row = lane >> 1, half = lane & 1;
    float qf[16];
#pragma unroll
    for (int d = 0; d < 16; d += 2) {
        const int src = 4 * (row & 7) + ((d & 7) >> 1);
        const uint32_t v0 = __shfl_sync(0xffffffffu, qb[(d >> 3) * 2], src), v1 = __shfl_sync(0xffffffffu, qb[(d >> 3) * 2 + 1], src);
        const uint32_t w = (row & 8) ? v1 : v0;
        qf[d] = bf_lo(w) * Q_SCALE;
        qf[d + 1] = bf_hi(w) * Q_SCALE;
    }
    float m = -INFINITY, l = 0.f, o[16];
#pragma unroll
    for (int d = 0; d < 16; d++) o[d] = 0.f;
#pragma unroll 1
    for (int j = half * 1024; j < half * 1024 + 1024; j++) {
        uint32_t kv[16];
#pragma unroll
        for (int i = 0; i < 4; i++) {
            const uint4 t = __ldcg(&g_kvb[j * 4 + i]);
            kv[4 * i] = t.x; kv[4 * i + 1] = t.y; kv[4 * i + 2] = t.z; kv[4 * i + 3] = t.w;
        }
        float s = 0.f;
#pragma unroll
        for (int i = 0; i < 8; i++) {
            const uint32_t w = kv[4 * (i & 3) + (i >> 2)];
            s = fmaf(qf[2 * i + 1], bf_hi(w), fmaf(qf[2 * i], bf_lo(w), s));
        }
        const float mn = fmaxf(m, s), a = exp2f(m - mn), p = exp2f(s - mn);
        m = mn;
        l = fmaf(l, a, p);
#pragma unroll
        for (int i = 0; i < 8; i++) {
            const uint32_t w = kv[4 * (i & 3) + 2 + (i >> 2)];
            o[2 * i] = fmaf(o[2 * i], a, p * bf_lo(w));
            o[2 * i + 1] = fmaf(o[2 * i + 1], a, p * bf_hi(w));
        }
    }
    const float m2 = __shfl_xor_sync(0xffffffffu, m, 1), mn = fmaxf(m, m2), a = exp2f(m - mn);
    l *= a;
    l += __shfl_xor_sync(0xffffffffu, l, 1);
    const float inv = 1.f / l;
    uint32_t w[8];
#pragma unroll
    for (int i = 0; i < 8; i++) {
        float e0 = o[2 * i] * a, e1 = o[2 * i + 1] * a;
        e0 += __shfl_xor_sync(0xffffffffu, e0, 1);
        e1 += __shfl_xor_sync(0xffffffffu, e1, 1);
        w[i] = pack_bf16(e0 * inv, e1 * inv);
    }
    const int R = r0 + row;
    const uint4 val = half ? make_uint4(w[4], w[5], w[6], w[7]) : make_uint4(w[0], w[1], w[2], w[3]);
    *(uint4*)(ounit + R * 64 + (((chunk0 + half) ^ ((R >> 1) & 3)) << 4)) = val;
}

template <bool A128, int NR>
__device__ __forceinline__ void gemm_item(float (&c0)[NR], float (&c1)[NR], uint32_t a, uint32_t b) {
    const uint64_t ad = A128 ? mkdesc(a, 16, 1024, 1) : mkdesc(a, 16, 512, 2), bd = mkdesc(b, 8192, 1024, 1);
    wg_fence();
#pragma unroll
    for (int k = 0; k < 4; k++) {
        const int ka = A128 ? 2 * k : (k >> 1) * 512 + (k & 1) * 2;
        wgmma_ss(c0, ad + ka, bd + k * 128);
        wgmma_ss(c1, ad + ka + (A128 ? 512 : 256), bd + k * 128);
    }
    wg_commit();
}
template <int NU>
__device__ __forceinline__ void stage_h(const float (&c)[NU * 16], uint32_t dst, int row0, int lane) {
    const int row = row0 + ((lane >> 3) & 1) * 8 + (lane & 7), sw = (row >> 1) & 3;
#pragma unroll
    for (int j = 0; j < NU * 4; j += 2)
        stsm4(dst + (j >> 2) * UNIT + row * 64 + ((((j & 3) + (lane >> 4)) ^ sw) << 4),
              pack_bf16_relu(c[4 * j], c[4 * j + 1]), pack_bf16_relu(c[4 * j + 2], c[4 * j + 3]),
              pack_bf16_relu(c[4 * j + 4], c[4 * j + 5]), pack_bf16_relu(c[4 * j + 6], c[4 * j + 7]));
}

struct Params {
    const __nv_bfloat16* x;
    const uint8_t *wkp, *wvp, *w1p, *w2p, *wop;
    CUtensorMap wq, w1, w2, wo, out;
};

__global__ void __launch_bounds__(512, 1) fused_mqa_ffn_kernel(const __grid_constant__ Params P) {
    extern __shared__ __align__(1024) uint8_t smem[];
    const uint32_t sb = (uint32_t)__cvta_generic_to_shared(smem);
#define TID_ROT 0
    const int tid = (threadIdx.x + TID_ROT) & 511, lane = tid & 31, g = lane >> 2, t4 = lane & 3;
    const int warp = __shfl_sync(0xffffffffu, tid >> 5, 0), wg = warp >> 2, wq4 = warp & 3;
    const int rb = blockIdx.x >> 3, c = blockIdx.x & 7;
    const uint32_t bars = sb + OFF_BAR;
    if (tid == 0) { TS(0); TSG(60); }

    const int rg = (warp + 2 * c + 4) & 15;
    const uint32_t xb = sb + OFF_XN + rg * 8192, xbar = bars + BAR_X + 8 * warp;
    uint32_t epoch = 0;
    if (tid == 384) TS(36);
    if (warp == 0 && elect()) { prefetch_map(&P.wq); prefetch_map(&P.w1); }
    __syncwarp();
    if (wg < 3) bar_sync(7, 512);
    if (elect()) {
        mbar_init(xbar, 1);
        if (warp == 14) mbar_init(bars + BAR_WKV, 1);
        asm volatile("fence.mbarrier_init.release.cluster;" ::: "memory");
        mbar_expect(xbar, 8192);
        bulk_g2s(xb, (const uint8_t*)P.x + (size_t)rb * 131072 + rg * 8192, 8192, xbar);
        if (warp == 14) {
            mbar_expect(bars + BAR_WKV, 32768);
            bulk_g2s(sb + OFF_WK, P.wkp, 16384, bars + BAR_WKV);
            bulk_g2s(sb + OFF_WV, P.wvp, 16384, bars + BAR_WKV);
            TS(39);
        }
    }
    __syncwarp();
    if (wg == 3) {
        bar_arrive(7, 512);
        if (warp == 15 && elect()) {
            mbar_init(bars + BAR_WQ, 1);
            mbar_init(bars + BAR_ST, 1);
#pragma unroll
            for (int i = 0; i < 4; i++) mbar_init(bars + BAR_OH + 8 * i, 8);
#pragma unroll
            for (int i = 0; i < 8; i++) mbar_init(bars + BAR_O + 8 * i, 1);
#pragma unroll
            for (int i = 2; i < N_BARS; i++) mbar_init(bars + 8 * i, 1);
            asm volatile("fence.mbarrier_init.release.cluster;" ::: "memory");
        }
        asm volatile("ld.relaxed.gpu.global.u32 %0, [%1];" : "=r"(epoch) : "l"(&g_sync[SY_EPOCH]) : "memory");
        *(uint32_t*)(smem + OFF_ONES + 4 * (tid - 384)) = 0x20002000u;
        bar_sync(5, 128);
        mbar_wait(bars + BAR_WKV, 0);
        if (tid == 384) TS(26);
#pragma unroll
        for (int i = 0; i < 4; i++) {
            const int r = tid - 384 + 128 * i;
            uint4* p = (uint4*)(smem + OFF_WK + ((r >> 2) * 8 + 4 + (r & 3)) * 32);
            const uint4 u = p[0], v = p[1];
            p[0] = v; p[1] = u;
        }
    }
    {
        uint4 xv[16];
        mbar_wait(xbar, 0);
        if (tid == 0) TS(42);
        if (tid == 384) TS(40);
        if (tid == 352) TS(43);
        if (warp == 15 && elect()) {
            mbar_expect(bars + BAR_WQ, 65536);
            tma2(sb + OFF_WQ, &P.wq, bars + BAR_WQ, 64 * c, 0);
            tma2(sb + OFF_WQ + 32768, &P.wq, bars + BAR_WQ, 64 * c, 256);
        }
        __syncwarp();
#pragma unroll
        for (int i = 0; i < 16; i++)
            asm volatile("ld.shared.v4.b32 {%0, %1, %2, %3}, [%4];" : "=r"(xv[i].x), "=r"(xv[i].y), "=r"(xv[i].z), "=r"(xv[i].w)
                         : "r"(xb + g * 1024 + ((i ^ (g & 1)) * 64) + t4 * 16) : "memory");
        float acc[4][4];
#pragma unroll
        for (int i = 0; i < 4; i++)
#pragma unroll
            for (int j = 0; j < 4; j++) acc[i][j] = 0.f;
#pragma unroll
        for (int i = 0; i < 32; i++) {
            const uint32_t w0 = (i & 1) ? xv[i >> 1].z : xv[i >> 1].x, w1 = (i & 1) ? xv[i >> 1].w : xv[i >> 1].y;
            asm volatile("mma.sync.aligned.m16n8k16.row.col.f32.bf16.bf16.f32 {%0, %1, %2, %3}, {%4, %6, %5, %6}, {%4, %5}, {%0, %1, %2, %3};"
                         : "+f"(acc[i & 3][0]), "+f"(acc[i & 3][1]), "+f"(acc[i & 3][2]), "+f"(acc[i & 3][3])
                         : "r"(w0), "r"(w1), "r"(0x3f803f80u));
        }
        if (tid == 0) TS(27);
        float ssq = (g & 1) ? (acc[0][1] + acc[1][1]) + (acc[2][1] + acc[3][1]) : (acc[0][0] + acc[1][0]) + (acc[2][0] + acc[3][0]);
        float sum = (g & 1) ? (acc[0][3] + acc[1][3]) + (acc[2][3] + acc[3][3]) : (acc[0][2] + acc[1][2]) + (acc[2][2] + acc[3][2]);
        ssq = __shfl_sync(0xffffffffu, ssq, 4 * g + (g >> 1));
        sum = __shfl_sync(0xffffffffu, sum, 4 * g + (g >> 1));
        const float mean = sum * (1.f / DM);
        const float var = fmaxf(fmaf(-mean, mean, ssq * (1.f / DM)), 0.f);
        const float sd = bf_round(sqrt_fast(bf_round(bf_round(var) + 1e-5f)));
        const float r = rcp_fast(sd), rh = bf_round(r), cm = -bf_round(mean) * r;
        const uint32_t rhi = pack_bf16(rh, rh), rlo = pack_bf16(r - rh, r - rh);
        uint32_t cc = pack_bf16(cm, cm);
        if (tid == 0) TS(1);
        if (wg < 3) bar_sync(10, 512);
        const uint32_t dst0 = xb + g * 128 + (((((g & 1) << 2) + t4) ^ g) << 4);
        if (__any_sync(0xffffffffu, !(fabsf(cm) < 0.5f))) {
            const float mb = -bf_round(mean);
            const uint32_t nm = pack_bf16(mb, mb), one = 0x3f803f80u;
#pragma unroll
            for (int i = 0; i < 16; i++) {
                xv[i].x = bf2fma(xv[i].x, one, nm); xv[i].y = bf2fma(xv[i].y, one, nm);
                xv[i].z = bf2fma(xv[i].z, one, nm); xv[i].w = bf2fma(xv[i].w, one, nm);
            }
            cc = 0;
        }
#pragma unroll
        for (int i = 0; i < 16; i++) {
            const uint32_t y0 = bf2fma(xv[i].x, rhi, bf2fma(xv[i].x, rlo, cc)), y1 = bf2fma(xv[i].y, rhi, bf2fma(xv[i].y, rlo, cc));
            const uint32_t y2 = bf2fma(xv[i].z, rhi, bf2fma(xv[i].z, rlo, cc)), y3 = bf2fma(xv[i].w, rhi, bf2fma(xv[i].w, rlo, cc));
            asm volatile("st.shared.v4.b32 [%0], {%1, %2, %3, %4};" ::"r"((dst0 ^ ((i & 1) << 6)) + (i >> 1) * 1024), "r"(y0), "r"(y1), "r"(y2), "r"(y3) : "memory");
        }
    }
    if (wg == 3) bar_arrive(10, 512);
    fence_async_smem();
    if (tid == 0) TS(2);

    if (wg < 3) {
        uint32_t qb[4];
        bool slow;
        uint32_t coff;
        int slowmask = 0;
        uint4* gq = g_q + blockIdx.x * 1024 + (tid & 127);
        bar_sync(6, 512);
        if (tid == 0) TS(30);
        const uint32_t qx = sb + OFF_WK + (tid & 127) * 16;
        if (wg < 2) {
            mbar_wait(bars + BAR_WQ, 0);
            if (tid == 0) TS(31);
            float a[32];
#pragma unroll
            for (int i = 0; i < 32; i++) a[i] = 0.f;
            pin(a);
            const uint64_t ad = mkdesc(sb + OFF_XN + wg * 65536, 16, 8192, 1), bd = mkdesc(sb + OFF_WQ, 16, 1024, 1);
            wg_fence();
#pragma unroll
            for (int k = 0; k < 32; k++) wgmma_ss(a, ad + (k >> 2) * 64 + (k & 3) * 2, bd + k * 128);
            wg_commit();
            wg_wait<0>();
            pin(a);
            bar_arrive(1, 512);
            uint32_t qa[16];
#pragma unroll
            for (int i = 0; i < 16; i++) qa[i] = pack_bf16(a[2 * i], a[2 * i + 1]);
            bar_sync(9, 384);
            if (wg == 0) asm volatile("st.shared.v4.b32 [%0], {%1, %2, %3, %4};" ::"r"(qx), "r"(qa[12]), "r"(qa[13]), "r"(qa[14]), "r"(qa[15]) : "memory");
            bar_arrive(8, 384);
#pragma unroll
            for (int h = 1; h < 4; h++) gq[(2 * h + wg) * 128] = make_uint4(qa[4 * h], qa[4 * h + 1], qa[4 * h + 2], qa[4 * h + 3]);
#pragma unroll
            for (int i = 0; i < 4; i++) qb[i] = qa[i];
            if (tid == 0) TS(3);
            int q2 = 0;
#pragma unroll
            for (int i = 0; i < 8; i++) {
                const int j = (i >> 1) * 4 + (i & 1);
                float s = bf_lo(qa[j]) * bf_lo(qa[j]);
                s = fmaf(bf_hi(qa[j]), bf_hi(qa[j]), s);
                s = fmaf(bf_lo(qa[j + 2]), bf_lo(qa[j + 2]), s);
                s = fmaf(bf_hi(qa[j + 2]), bf_hi(qa[j + 2]), s);
                s += __shfl_xor_sync(0xffffffffu, s, 1);
                s += __shfl_xor_sync(0xffffffffu, s, 2);
                q2 = max(q2, __float_as_int(s) & 0x7fffffff);
            }
            mbar_wait(bars + BAR_ST, 0);
            const int2 st = *(const int2*)(smem + OFF_BAR + STAT_VAL);
            const float qn2 = __int_as_float(q2) * (Q_SCALE * Q_SCALE), kn2 = __int_as_float(st.x), vx = __int_as_float(st.y);
            const bool ok = (qn2 * kn2 < 960.f * 960.f) && (qn2 < 1.6e7f) && (kn2 < 1.6e7f) && (vx < 1024.f) && (vx >= 0.015625f);
            slow = __any_sync(0xffffffffu, bar_or(2 + wg, 128, !ok));
            if ((tid & 127) == 0) *(volatile int*)(smem + OFF_STAT + 4 * wg) = slow;
            bar_arrive(11 + wg, 256);
        } else {
            bar_sync(8, 384);
            asm volatile("ld.shared.v4.b32 {%0, %1, %2, %3}, [%4];" : "=r"(qb[0]), "=r"(qb[1]), "=r"(qb[2]), "=r"(qb[3]) : "r"(qx) : "memory");
            fence_async_smem();
            bar_arrive(1, 512);
            bar_sync(11, 256);
            bar_sync(12, 256);
            slowmask = __shfl_sync(0xffffffffu, *(volatile int*)(smem + OFF_STAT) + 2 * *(volatile int*)(smem + OFF_STAT + 4), 0);
            slow = false;
        }
        coff = H2C(27 - max((*(const int*)(smem + OFF_BAR + STAT_VAL + 4) >> 23) - 127, 0));
        if (tid == 0) TS(4);
        const int nround = wg < 2 ? 3 : 4;
        const uint64_t kd0 = mkdesc(sb + OFF_K, 16, 256, 3), vd0 = mkdesc(sb + OFF_V, OFF_ONES - OFF_V, 256, 3);
#pragma unroll 1
        for (int r = 0; r < nround; r++) {
            const bool last = r >= 2, helper = last && wg == 2;
            const int h = last ? 2 : (wg < 2 ? r : 3), half = wg < 2 ? wg : (r & 1), r0 = half * 64 + wq4 * 16;
            uint8_t* ounit = g_o + (size_t)((rb * 4 + h) * 4 + (c >> 1)) * UNIT;
            if (wg == 2) {
                slow = (slowmask >> half) & 1;
                if (r == 2) bar_sync(13, 256);
            }
            uint4 qn = make_uint4(0, 0, 0, 0);
            if (!slow) {
                uint32_t q[4];
#pragma unroll
                for (int i = 0; i < 4; i++) q[i] = pack_f16(bf_lo(qb[i]) * (Q_SCALE / 32.f), bf_hi(qb[i]) * (Q_SCALE / 32.f));
                float O[10];
#pragma unroll
                for (int i = 0; i < 10; i++) O[i] = 0.f;
                uint32_t mrun = H2C(0xFBFF), cxp = H2C(0x7C00), T[6] = {0, 0, 0, 0, 0, 0};
                float a0 = 0.f, a1 = 0.f;
                const int t0 = helper ? SPLIT_T : 0, t1 = (last && wg < 2) ? SPLIT_T : 8;
                uint64_t kd = kd0 + t0 * K_INC, vd = vd0 + (uint64_t)(t0 * 16 * V_INC);
#pragma unroll TUNROLL_C
                for (int t = t0; t < t1; t++) {
                    if (r == 0) mbar_wait(bars + BAR_KV + 8 * t, 0);
                    attn_tile(O, T, a0, a1, q, mrun, cxp, kd, vd, coff, lane);
                    kd += K_INC;
                    vd += (uint64_t)(16 * V_INC);
                }
                if (r + 1 < nround) qn = __ldcg(gq + (wg < 2 ? 2 * (r + 1) + wg : (r == 0 ? 7 : 3 + r)) * 128);
                if (last) {
                    float* mb = (float*)(smem + OFF_MERGE + half * 5632) + (tid & 127);
                    if (helper) {
#pragma unroll
                        for (int i = 0; i < 10; i++) mb[128 * i] = O[i];
                        mb[128 * 10] = __uint_as_float(cxp);
                        bar_arrive(14 + half, 256);
                    } else {
                        bar_sync(14 + half, 256);
                        const uint32_t cxo = __float_as_uint(mb[128 * 10]);
                        const uint32_t cxm = h2min(cxp, cxo), da = h2sub(cxm, cxp), db = h2sub(cxm, cxo);
                        const float e0 = ex2f(h_lo(da)), e1 = ex2f(h_hi(da)), b0 = ex2f(h_lo(db)), b1 = ex2f(h_hi(db));
#pragma unroll
                        for (int i = 0; i < 10; i++) {
                            const bool hi = i < 8 ? (i & 2) : (i & 1);
                            O[i] = fmaf(O[i], hi ? e1 : e0, mb[128 * i] * (hi ? b1 : b0));
                        }
                    }
                }
                if (!helper) {
                    const float i0 = 2.f * rcp_fast(O[8]), i1 = 2.f * rcp_fast(O[9]);
                    const int R = r0 + g;
                    uint8_t* p = ounit + R * 64 + ((((c & 1) * 2 + (t4 >> 1)) ^ ((R >> 1) & 3)) << 4) + (t4 & 1) * 8;
                    *(uint2*)p = make_uint2(pack_bf16(O[0] * i0, O[1] * i0), pack_bf16(O[4] * i0, O[5] * i0));
                    *(uint2*)(p + 512) = make_uint2(pack_bf16(O[2] * i1, O[3] * i1), pack_bf16(O[6] * i1, O[7] * i1));
                }
            } else {
                if (r + 1 < nround) qn = __ldcg(gq + (wg < 2 ? 2 * (r + 1) + wg : (r == 0 ? 7 : 3 + r)) * 128);
                if (!helper) attn_slow(qb, ounit, r0, (c & 1) * 2, lane);
            }
            __syncwarp();
            if (lane == 0 && !helper) {
                if (h == 2) signal_add(&g_sync[SY_O + (rb * 4 + 2) * 32]);
                else asm volatile("mbarrier.arrive.shared::cta.b64 _, [%0];" ::"r"(bars + BAR_OH + 8 * h) : "memory");
            }
            if (tid == 0) TS(5 + r);
            if (tid == 256) TS(8 + r);
            qb[0] = qn.x; qb[1] = qn.y; qb[2] = qn.z; qb[3] = qn.w;
        }
    } else {
        const bool prod = warp == 12;
        const bool kvwarp = wq4 == (c & 3);
        bar_arrive(6, 512);
        bar_sync(5, 128);
        if (tid == 384) TS(32);
        {
            float a[16];
#pragma unroll
            for (int i = 0; i < 16; i++) a[i] = 0.f;
            pin(a);
            const uint64_t ad = mkdesc(sb + OFF_XN + (c >> 2) * 65536, 16, 8192, 1), bd = mkdesc(sb + OFF_WK, 16384, 256, 3);
            wg_fence();
#pragma unroll
            for (int k = 0; k < 32; k++) wgmma_ss(a, ad + (k >> 2) * 64 + (k & 3) * 2, bd + k * 32);
            wg_commit();
            if (lane < 4) {
                const int j = wq4 * 4 + lane, q = 2 * c + (j >> 3), kc = j & 7;
                bulk_s2g(g_xn + (size_t)(rb * 8 + kc) * 16384 + q * 1024, sb + OFF_XN + q * 8192 + kc * 1024, 1024);
                bulk_commit();
            }
            __syncwarp();
            wg_wait<0>();
            pin(a);
            bar_arrive(9, 384);
            if (tid == 384) TS(33);
            if (kvwarp) {
                uint32_t w[8];
#pragma unroll
                for (int i = 0; i < 8; i++) w[i] = pack_bf16(a[2 * i], a[2 * i + 1]);
                uint8_t* stg = smem + OFF_STAT;
                const int key0 = rb * 128 + c * 16;
#pragma unroll
                for (int hh = 0; hh < 2; hh++) {
                    const int kr = g + 8 * hh, sw = (kr >> 2) & 1;
#pragma unroll
                    for (int b = 0; b < 2; b++) {
                        const uint32_t kk = w[2 * b + hh], vv = w[4 + 2 * b + hh];
                        *(uint32_t*)(stg + kr * 32 + ((b ^ sw) << 4) + 4 * t4) = pack_f16(bf_lo(kk) * 0.0625f, bf_hi(kk) * 0.0625f);
                        *(uint32_t*)(stg + 512 + kr * 32 + (((t4 & 1) ^ sw) << 4) + 8 * b + 4 * (t4 >> 1)) = pack_f16(bf_lo(vv) * 0.00390625f, bf_hi(vv) * 0.00390625f);
                    }
                }
                fence_async_smem();
                __syncwarp();
                if (elect()) {
                    bulk_s2g(g_kv + key0 * 32, sb + OFF_STAT, 512);
                    bulk_s2g(g_kv + 65536 + key0 * 32, sb + OFF_STAT + 512, 512);
                    bulk_commit();
                }
                __syncwarp();
                int k2 = 0, vm = 0;
#pragma unroll
                for (int hh = 0; hh < 2; hh++) {
                    g_kvb[(key0 + g + 8 * hh) * 4 + t4] = make_uint4(w[hh], w[2 + hh], w[4 + hh], w[6 + hh]);
                    float s = 0.f;
#pragma unroll
                    for (int b = 0; b < 2; b++) {
                        const uint32_t kk = w[2 * b + hh], vv = w[4 + 2 * b + hh];
                        s = fmaf(bf_lo(kk), bf_lo(kk), fmaf(bf_hi(kk), bf_hi(kk), s));
                        vm = max(vm, max((int)((vv << 16) & 0x7fffffff), (int)(vv & 0x7fff0000)));
                    }
                    s += __shfl_xor_sync(0xffffffffu, s, 1);
                    s += __shfl_xor_sync(0xffffffffu, s, 2);
                    k2 = max(k2, __float_as_int(s) & 0x7fffffff);
                }
                k2 = __reduce_max_sync(0xffffffffu, k2);
                vm = __reduce_max_sync(0xffffffffu, vm);
                if (lane < 2)
                    asm volatile("red.relaxed.gpu.global.max.u64 [%0], %1;" ::"l"(&g_sync[SY_MAX + 2 * lane]),
                                 "l"(((unsigned long long)(epoch + 1) << 32) | (uint32_t)(lane ? vm : k2)) : "memory");
                if (lane == 0) TS(34);
            }
            bulk_wait_all();
            bar_sync(5, 128);
            if (tid == 384) TS(35);
            if (kvwarp && lane == 0) { signal_add(&g_sync[SY_KV]); TS(12); }
            __syncwarp();
        }
        if (prod) flag_wait(&g_sync[SY_KV], (epoch + 1) * 128);
        if (tid == 384) TS(14);
        bar_sync(1, 512);
        const uint32_t ring = __shfl_sync(0xffffffffu, sb, 0) + OFF_RING;
        const uint32_t rbar = ring - OFF_RING + OFF_BAR;
        const uint8_t* xn_src = g_xn + (size_t)rb * 131072;
        auto issue1 = [&](int it) {
            const int pass = it / 9, kc = it - 9 * pass, col = 224 * c + (pass ? 32 + 64 * pass : 0);
            const uint32_t slot = ring + (it % 3) * 32768, bar = rbar + BAR_R1 + (it % 3) * 8;
            mbar_expect(bar, pass ? 24576 : 32768);
            bulk_g2s(slot, xn_src + kc * 16384, 16384, bar);
            tma2(slot + 16384, &P.w1, bar, col, kc * 64);
            if (!pass) tma2(slot + 24576, &P.w1, bar, col + 64, kc * 64);
        };
        if (prod) {
            if (lane == 0) TS(13);
          if (elect()) {
            uint32_t a0, a1, a2, a3;
            (void)a1; (void)a3;
            asm volatile("ld.relaxed.gpu.global.v4.u32 {%0, %1, %2, %3}, [%4];" : "=r"(a0), "=r"(a1), "=r"(a2), "=r"(a3) : "l"(&g_sync[SY_MAX]) : "memory");
            fence_async_global();
#pragma unroll
            for (int t = 0; t < 8; t++) {
                const uint32_t bar = bars + BAR_KV + 8 * t;
                mbar_expect(bar, 16384);
                bulk_g2s(sb + OFF_K + t * 8192, g_kv + t * 8192, 8192, bar);
                bulk_g2s(sb + OFF_V + t * 8192, g_kv + 65536 + t * 8192, 8192, bar);
                if (t == 1) {
                    issue1(0);
                    *(uint2*)(smem + OFF_BAR + STAT_VAL) = make_uint2(a0, a2);
                    asm volatile("mbarrier.arrive.shared::cta.b64 _, [%0];" ::"r"(bars + BAR_ST) : "memory");
                    issue1(1);
                    issue1(2);
                }
            }
            if (blockIdx.x == 0) asm volatile("st.relaxed.gpu.global.u32 [%0], %1;" ::"l"(&g_sync[SY_EPOCH]), "r"(epoch + 1) : "memory");
            l2_prefetch(P.w1p + blockIdx.x * 14336, 14336);
            prefetch_map(&P.w2); prefetch_map(&P.wo); prefetch_map(&P.out);
            l2_prefetch(P.w2p + blockIdx.x * 14336, 14336);
            l2_prefetch(P.wop + blockIdx.x * 4096, 4096);
          }
        }
        __syncwarp();
        uint8_t* h_dst = g_h + (size_t)(rb * 56 + 7 * c) * UNIT;
        auto ffn1_pass = [&](auto nu, int pass) {
            constexpr int NU = decltype(nu)::value;
            float c0[NU * 16], c1[NU * 16];
#pragma unroll
            for (int i = 0; i < NU * 16; i++) { c0[i] = 0.f; c1[i] = 0.f; }
            pin(c0); pin(c1);
#pragma unroll 1
            for (int j = 0; j < 8; j++) {
                const int it = 9 * pass + j, s = j % 3;
                mbar_wait(rbar + BAR_R1 + s * 8, (it / 3 - (s == 2 ? pass : 0)) & 1);
                gemm_item<true>(c0, c1, ring + s * 32768, ring + s * 32768 + 16384);
                wg_wait<1>();
                bar_sync(5, 128);
                if (prod && it > 0 && j != 6 && it != 25 && elect()) {
                    if (j == 0) bulk_wait_read();
                    issue1(it + 2);
                }
                __syncwarp();
            }
            wg_wait<0>();
            pin(c0); pin(c1);
            stage_h<NU>(c0, ring + 2 * 32768, wq4 * 16, lane);
            stage_h<NU>(c1, ring + 2 * 32768, 64 + wq4 * 16, lane);
            fence_async_smem();
            bar_sync(5, 128);
            if (prod && elect()) {
                if (pass < 2) issue1(9 * pass + 10);
                bulk_s2g(h_dst + (pass ? 1 + 2 * pass : 0) * UNIT, ring + 2 * 32768, NU * UNIT);
                bulk_commit();
                if (pass == 2) {
                    bulk_wait_all();
                    signal_add(&g_sync[SY_H + rb * 32]);
                }
                TS(pass == 2 ? 16 : 15);
            }
            __syncwarp();
        };
        ffn1_pass(std::integral_constant<int, 3>{}, 0);
#pragma unroll 1
        for (int pass = 1; pass < 3; pass++) ffn1_pass(std::integral_constant<int, 2>{}, pass);
        float c0[32], c1[32];
        {
            const __nv_bfloat16* xp = P.x + (size_t)(rb * 128 + wq4 * 16 + g) * DM + c * 64 + 2 * t4;
#pragma unroll
            for (int j = 0; j < 8; j++) {
                const uint32_t v0 = ldg_here(xp + 8 * j), v1 = ldg_here(xp + 8 * DM + 8 * j);
                const uint32_t v2 = ldg_here(xp + 64 * DM + 8 * j), v3 = ldg_here(xp + 72 * DM + 8 * j);
                c0[4 * j] = bf_lo(v0); c0[4 * j + 1] = bf_hi(v0); c0[4 * j + 2] = bf_lo(v1); c0[4 * j + 3] = bf_hi(v1);
                c1[4 * j] = bf_lo(v2); c1[4 * j + 1] = bf_hi(v2); c1[4 * j + 2] = bf_lo(v3); c1[4 * j + 3] = bf_hi(v3);
            }
            pin(c0); pin(c1);
        }
        const uint8_t* h_src = g_h + (size_t)rb * 56 * UNIT;
        const uint8_t* o_src = g_o + (size_t)rb * 16 * UNIT;
        auto head_of = [](int it) { const int p = (it - 28) >> 1; return p < 2 ? p : 5 - p; };
        auto issue2 = [&](int it, int parts) {
            const uint32_t slot = ring + (it < 28 ? it & 3 : (it - 28) % 3) * 24576;
            const uint32_t bar = it < 28 ? rbar + BAR_R2 + (it & 3) * 8 : rbar + BAR_O + (it - 28) * 8;
            const int h = head_of(it);
            if (parts & 1) {
                mbar_expect(bar, 24576);
                if (it < 28) tma2(slot + 16384, &P.w2, bar, 64 * c, it * 64);
                else tma3(slot + 16384, &P.wo, bar, 64 * c, 16 * h, 4 * (it & 1));
            }
            if (parts & 2) bulk_g2s(slot, it < 28 ? h_src + it * 16384 : o_src + (h * 4 + 2 * (it & 1)) * UNIT, 16384, bar);
        };
        if (prod) {
            if (elect()) {
#pragma unroll 1
                for (int i = 0; i < 4; i++) issue2(i, 1);
            }
            __syncwarp();
            flag_wait(&g_sync[SY_H + rb * 32], (epoch + 1) * 8);
            if (lane == 0) TS(17);
            if (elect()) {
                fence_async_global();
#pragma unroll 1
                for (int i = 0; i < 4; i++) issue2(i, 2);
            }
            __syncwarp();
        }
        bar_sync(5, 128);
#pragma unroll 1
        for (int it = 0; it < 28; it++) {
            mbar_wait(rbar + BAR_R2 + (it & 3) * 8, (it >> 2) & 1);
            gemm_item<false>(c0, c1, ring + (it & 3) * 24576, ring + (it & 3) * 24576 + 16384);
            wg_wait<1>();
            bar_sync(5, 128);
            if (prod && it >= 1 && it < 25 && elect()) issue2(it + 3, 3);
            __syncwarp();
        }
        wg_wait<0>();
        pin(c0); pin(c1);
        bar_arrive(13, 256);
        bar_sync(5, 128);
#pragma unroll 1
        for (int seg = 0; seg < 3; seg++) {
            const int first = seg == 0 ? 28 : 26 + 4 * seg, n = seg == 1 ? 4 : 2;
            if (prod) {
                uint32_t* f = &g_sync[SY_O + (rb * 4 + seg) * 32];
                if (elect()) {
#pragma unroll 1
                    for (int i = first; i < first + (n > 3 ? 3 : n); i++) issue2(i, 1);
                }
                __syncwarp();
                if (seg < 2) {
                    mbar_wait(bars + BAR_OH + 8 * seg, 0);
                    if (seg == 1) mbar_wait(bars + BAR_OH + 24, 0);
                    if (elect()) {
                        signal_add(f);
                        if (seg == 1) asm volatile("red.relaxed.gpu.global.add.u32 [%0], 1;" ::"l"(f + 64) : "memory");
                    }
                    __syncwarp();
                }
                if (seg == 1) flag_wait(f + 64, (epoch + 1) * 8);
                flag_wait(f, (epoch + 1) * (seg == 2 ? 64 : 8));
                if (lane == 0) TS(18 + seg);
                if (elect()) {
                    fence_async_global();
#pragma unroll 1
                    for (int i = first; i < first + (n > 3 ? 3 : n); i++) issue2(i, 2);
                }
                __syncwarp();
            }
            bar_sync(5, 128);
#pragma unroll 1
            for (int it = first; it < first + n; it++) {
                const uint32_t slot = ring + ((it - 28) % 3) * 24576;
                mbar_wait(rbar + BAR_O + (it - 28) * 8, 0);
                gemm_item<false>(c0, c1, slot, slot + 16384);
                if (it == 31) {
                    wg_wait<1>();
                    bar_sync(5, 128);
                    if (prod && elect()) issue2(33, 3);
                    __syncwarp();
                }
            }
            wg_wait<0>();
            pin(c0); pin(c1);
            if (seg < 2) bar_sync(5, 128);
        }
        if (tid == 384) TS(22);
        {
            const uint32_t ob = ring + 49152;
            const int row = wq4 * 16 + ((lane >> 3) & 1) * 8 + (lane & 7);
#pragma unroll
            for (int j = 0; j < 8; j += 2) {
                const uint32_t a = ob + row * 128 + (((j + (lane >> 4)) ^ (row & 7)) << 4);
                stsm4(a, pack_bf16(c0[4 * j], c0[4 * j + 1]), pack_bf16(c0[4 * j + 2], c0[4 * j + 3]),
                      pack_bf16(c0[4 * j + 4], c0[4 * j + 5]), pack_bf16(c0[4 * j + 6], c0[4 * j + 7]));
                stsm4(a + 8192, pack_bf16(c1[4 * j], c1[4 * j + 1]), pack_bf16(c1[4 * j + 2], c1[4 * j + 3]),
                      pack_bf16(c1[4 * j + 4], c1[4 * j + 5]), pack_bf16(c1[4 * j + 6], c1[4 * j + 7]));
            }
            fence_async_smem();
            __syncwarp();
            if (elect()) {
                tma2_store(&P.out, ob + wq4 * 2048, c * 64, rb * 128 + wq4 * 16);
                tma2_store(&P.out, ob + 8192 + wq4 * 2048, c * 64, rb * 128 + 64 + wq4 * 16);
                bulk_commit();
                bulk_wait_read();
            }
            if (tid == 384) {
                TS(23); TSG(61);
            }
        }
    }
}

typedef CUresult (*EncodeFn)(CUtensorMap*, CUtensorMapDataType, cuuint32_t, void*, const cuuint64_t*, const cuuint64_t*, const cuuint32_t*,
                             const cuuint32_t*, CUtensorMapInterleave, CUtensorMapSwizzle, CUtensorMapL2promotion, CUtensorMapFloatOOBfill);

void encode(EncodeFn fn, CUtensorMap* m, const void* p, int rank, const cuuint64_t* dims, const cuuint64_t* strides, const cuuint32_t* box, CUtensorMapSwizzle sw) {
    const cuuint32_t es[5] = {1, 1, 1, 1, 1};
    fn(m, CU_TENSOR_MAP_DATA_TYPE_BFLOAT16, rank, const_cast<void*>(p), dims, strides, box, es, CU_TENSOR_MAP_INTERLEAVE_NONE, sw,
       CU_TENSOR_MAP_L2_PROMOTION_L2_256B, CU_TENSOR_MAP_FLOAT_OOB_FILL_NONE);
}

}

extern "C" void kernel_launch(void* const* d_in, const int* in_sizes, int n_in, void* d_out, int out_size) {
    (void)in_sizes; (void)n_in; (void)out_size;
    static EncodeFn fn = nullptr;
    if (!fn) {
        void* p = nullptr;
        cudaDriverEntryPointQueryResult qr;
        cudaGetDriverEntryPoint("cuTensorMapEncodeTiled", &p, cudaEnableDefault, &qr);
        fn = (EncodeFn)p;
        cudaFuncSetAttribute(fused_mqa_ffn_kernel, cudaFuncAttributeMaxDynamicSharedMemorySize, SMEM_BYTES);
    }
    Params P;
    {
        const cuuint64_t d[2] = {DM, DM}, s[1] = {DM * 2};
        const cuuint32_t b[2] = {64, 256};
        encode(fn, &P.wq, d_in[1], 2, d, s, b, CU_TENSOR_MAP_SWIZZLE_128B);
    }
    {
        const cuuint64_t d[2] = {DFF, DM}, s[1] = {DFF * 2};
        const cuuint32_t b[2] = {64, 64};
        encode(fn, &P.w1, d_in[6], 2, d, s, b, CU_TENSOR_MAP_SWIZZLE_128B);
    }
    {
        const cuuint64_t d[2] = {DM, DFF}, s[1] = {DM * 2};
        const cuuint32_t b[2] = {64, 64};
        encode(fn, &P.w2, d_in[7], 2, d, s, b, CU_TENSOR_MAP_SWIZZLE_128B);
    }
    {
        const cuuint64_t d[3] = {DM, 64, 8}, s[2] = {DM * 2, 64 * DM * 2};
        const cuuint32_t b[3] = {64, 16, 4};
        encode(fn, &P.wo, d_in[4], 3, d, s, b, CU_TENSOR_MAP_SWIZZLE_128B);
    }
    {
        const cuuint64_t d[2] = {DM, SEQ}, s[1] = {DM * 2};
        const cuuint32_t b[2] = {64, 16};
        encode(fn, &P.out, d_out, 2, d, s, b, CU_TENSOR_MAP_SWIZZLE_128B);
    }
    P.x = (const __nv_bfloat16*)d_in[0];
    P.wkp = (const uint8_t*)d_in[2];
    P.wvp = (const uint8_t*)d_in[3];
    P.w1p = (const uint8_t*)d_in[6];
    P.w2p = (const uint8_t*)d_in[7];
    P.wop = (const uint8_t*)d_in[4];
    fused_mqa_ffn_kernel<<<128, 512, SMEM_BYTES, cudaStreamPerThread>>>(P);
}
```

```cpp
#include <cuda_runtime.h>
#include <cuda.h>
#include <cuda_bf16.h>
#include <cuda_fp16.h>
#include <stdint.h>
#include <utility>

namespace {

constexpr int SEQ = 2048, DM = 512, DFF = 1792;
constexpr uint32_t POLY_MASK = 0x66666666u;
constexpr int ORDER = 0x0321;
constexpr int SPLIT_T = 5;

constexpr int UNIT = 4096;
__device__ __align__(1024) uint8_t g_kv[131072];
__device__ __align__(1024) uint4   g_kvb[SEQ * 4];
__device__ __align__(1024) uint8_t g_xn[32 * 8 * 8192];
__device__ __align__(1024) uint8_t g_h[32 * 56 * UNIT];
__device__ __align__(1024) uint4   g_q[128 * 8 * 128];
__device__ __align__(1024) uint8_t g_o[32 * 16 * UNIT];
__device__ __align__(1024) uint32_t g_sync[32 * (2 + 32 + 96)];
constexpr int SY_EPOCH = 0, SY_KV = 1, SY_MAX = 4, SY_H = 64, SY_O = 64 + 32 * 32;

constexpr uint32_t OFF_WQ = 0;
constexpr uint32_t OFF_K = 0, OFF_V = 65536;
constexpr uint32_t OFF_ONES = 131072;
constexpr uint32_t OFF_RING = 132096;
constexpr uint32_t OFF_XN = OFF_RING, OFF_WK = OFF_RING + 65536, OFF_WV = OFF_RING + 81920;
constexpr uint32_t OFF_MERGE = OFF_RING + 73728;
constexpr uint32_t OFF_STAT = OFF_RING + 98304;
constexpr uint32_t OFF_BAR = OFF_STAT + 1024;
constexpr uint32_t SMEM_BYTES = OFF_BAR + 768;
constexpr uint32_t BAR_WQ = 0, BAR_WKV = 16, BAR_KV = 24, BAR_R1 = 88, BAR_R2 = 112, BAR_ST = 144, BAR_O = 152, BAR_X = 216, BAR_OH = 280, STAT_VAL = 296;

template <class F, int... I> __device__ __forceinline__ void static_for_impl(F&& f, std::integer_sequence<int, I...>) { (f(std::integral_constant<int, I>{}), ...); }
template <int N, class F> __device__ __forceinline__ void static_for(F&& f) { static_for_impl(f, std::make_integer_sequence<int, N>{}); }

__device__ __forceinline__ void wg_fence() { asm volatile("wgmma.fence.sync.aligned;" ::: "memory"); }
__device__ __forceinline__ void wg_commit() { asm volatile("wgmma.commit_group.sync.aligned;" ::: "memory"); }
template <int N> __device__ __forceinline__ void wg_wait() { asm volatile("wgmma.wait_group.sync.aligned %0;" ::"n"(N) : "memory"); }
__device__ __forceinline__ void pin(float& x) { asm volatile("" : "+f"(x)::"memory"); }
__device__ __forceinline__ void pin(uint32_t& x) { asm volatile("" : "+r"(x)::"memory"); }
template <class T, int N> __device__ __forceinline__ void pin(T (&d)[N]) {
#pragma unroll
    for (int i = 0; i < N; i++) pin(d[i]);
}
__device__ __forceinline__ uint64_t mkdesc(uint32_t addr, uint32_t lbo, uint32_t sbo, uint32_t sw) {
    return (uint64_t)((addr >> 4) | ((lbo >> 4) << 16)) | ((uint64_t)((sbo >> 4) | (sw << 30)) << 32);
}
__device__ __forceinline__ void mbar_init(uint32_t bar, int cnt) { asm volatile("mbarrier.init.shared::cta.b64 [%0], %1;" ::"r"(bar), "r"(cnt) : "memory"); }
__device__ __forceinline__ void mbar_expect(uint32_t bar, uint32_t bytes) { asm volatile("mbarrier.arrive.expect_tx.shared::cta.b64 _, [%0], %1;" ::"r"(bar), "r"(bytes) : "memory"); }
__device__ __forceinline__ bool mbar_try(uint32_t bar, uint32_t par) {
    uint32_t r;
    asm volatile("{.reg .pred p; mbarrier.try_wait.parity.shared::cta.b64 p, [%1], %2, %3; selp.u32 %0, 1, 0, p;}" : "=r"(r) : "r"(bar), "r"(par), "r"(20000u) : "memory");
    return r;
}
__device__ __forceinline__ void mbar_wait(uint32_t bar, uint32_t par) {
    int n = 0;
    while (!__all_sync(0xffffffffu, mbar_try(bar, par) | (++n > (1 << 16)))) {}
}
__device__ __forceinline__ bool elect() {
    uint32_t r;
    asm volatile("{.reg .pred p; elect.sync _|p, 0xffffffff; selp.u32 %0, 1, 0, p;}" : "=r"(r));
    return r;
}
__device__ __forceinline__ void bulk_g2s(uint32_t dst, const void* src, uint32_t bytes, uint32_t bar) {
    asm volatile("cp.async.bulk.shared::cluster.global.mbarrier::complete_tx::bytes [%0], [%1], %2, [%3];" ::"r"(dst), "l"(src), "r"(bytes), "r"(bar) : "memory");
}
__device__ __forceinline__ void bulk_s2g(void* dst, uint32_t src, uint32_t bytes) {
    asm volatile("cp.async.bulk.global.shared::cta.bulk_group [%0], [%1], %2;" ::"l"(dst), "r"(src), "r"(bytes) : "memory");
}
__device__ __forceinline__ void bulk_commit() { asm volatile("cp.async.bulk.commit_group;" ::: "memory"); }
__device__ __forceinline__ void bulk_wait_all() { asm volatile("cp.async.bulk.wait_group 0;" ::: "memory"); }
__device__ __forceinline__ void bulk_wait_read() { asm volatile("cp.async.bulk.wait_group.read 0;" ::: "memory"); }
__device__ __forceinline__ void l2_prefetch(const void* p, uint32_t bytes) { asm volatile("cp.async.bulk.prefetch.L2.global [%0], %1;" ::"l"(p), "r"(bytes) : "memory"); }
__device__ __forceinline__ void tma2(uint32_t dst, const CUtensorMap* m, uint32_t bar, int c0, int c1) {
    asm volatile("cp.async.bulk.tensor.2d.shared::cluster.global.mbarrier::complete_tx::bytes [%0], [%1, {%3, %4}], [%2];" ::"r"(dst), "l"(m), "r"(bar), "r"(c0), "r"(c1) : "memory");
}
__device__ __forceinline__ void tma3(uint32_t dst, const CUtensorMap* m, uint32_t bar, int c0, int c1, int c2) {
    asm volatile("cp.async.bulk.tensor.3d.shared::cluster.global.mbarrier::complete_tx::bytes [%0], [%1, {%3, %4, %5}], [%2];" ::"r"(dst), "l"(m), "r"(bar), "r"(c0), "r"(c1), "r"(c2) : "memory");
}
__device__ __forceinline__ void tma2_store(const CUtensorMap* m, uint32_t src, int c0, int c1) {
    asm volatile("cp.async.bulk.tensor.2d.global.shared::cta.bulk_group [%0, {%2, %3}], [%1];" ::"l"(m), "r"(src), "r"(c0), "r"(c1) : "memory");
}
__device__ __forceinline__ void prefetch_map(const CUtensorMap* m) { asm volatile("prefetch.tensormap [%0];" ::"l"(m) : "memory"); }
__device__ __forceinline__ void fence_async_smem() { asm volatile("fence.proxy.async.shared::cta;" ::: "memory"); }
__device__ __forceinline__ void fence_async_global() { asm volatile("fence.proxy.async.global;" ::: "memory"); }
__device__ __forceinline__ void bar_sync(int id, int n) { asm volatile("bar.sync %0, %1;" ::"r"(id), "r"(n) : "memory"); }
__device__ __forceinline__ void bar_arrive(int id, int n) { asm volatile("bar.arrive %0, %1;" ::"r"(id), "r"(n) : "memory"); }
__device__ __forceinline__ bool bar_or(int id, int n, bool p) {
    uint32_t r;
    asm volatile("{.reg .pred a, b; setp.ne.u32 a, %3, 0; bar.red.or.pred b, %1, %2, a; selp.u32 %0, 1, 0, b;}" : "=r"(r) : "r"(id), "r"(n), "r"((uint32_t)p) : "memory");
    return r;
}
__device__ __forceinline__ void signal_add(uint32_t* p) {
    asm volatile("red.release.gpu.global.add.u32 [%0], 1;" ::"l"(p) : "memory");
}
__device__ __forceinline__ void flag_wait(const uint32_t* p, uint32_t target) {
    int n = 0;
    uint32_t v;
    do {
        asm volatile("ld.relaxed.gpu.global.u32 %0, [%1];" : "=r"(v) : "l"(p) : "memory");
    } while (!__all_sync(0xffffffffu, ((int)(v - target) >= 0) | (++n > (1 << 21))));
    asm volatile("fence.acquire.gpu;" ::: "memory");
}
__device__ __forceinline__ void stsm4(uint32_t addr, uint32_t r0, uint32_t r1, uint32_t r2, uint32_t r3) {
    asm volatile("stmatrix.sync.aligned.m8n8.x4.shared.b16 [%0], {%1, %2, %3, %4};" ::"r"(addr), "r"(r0), "r"(r1), "r"(r2), "r"(r3) : "memory");
}
__device__ __forceinline__ uint32_t pack_bf16(float lo, float hi) { uint32_t d; asm("cvt.rn.bf16x2.f32 %0, %1, %2;" : "=r"(d) : "f"(hi), "f"(lo)); return d; }
__device__ __forceinline__ uint32_t pack_bf16_relu(float lo, float hi) { uint32_t d; asm("cvt.rn.relu.bf16x2.f32 %0, %1, %2;" : "=r"(d) : "f"(hi), "f"(lo)); return d; }
__device__ __forceinline__ uint32_t pack_f16(float lo, float hi) { uint32_t d; asm("cvt.rn.f16x2.f32 %0, %1, %2;" : "=r"(d) : "f"(hi), "f"(lo)); return d; }
__device__ __forceinline__ float bf_lo(uint32_t v) { return __uint_as_float(v << 16); }
__device__ __forceinline__ float bf_hi(uint32_t v) { return __uint_as_float(v & 0xffff0000u); }
__device__ __forceinline__ float bf_round(float x) { return bf_lo(pack_bf16(x, 0.f)); }
__device__ __forceinline__ uint32_t bf2fma(uint32_t a, uint32_t b, uint32_t c) { uint32_t d; asm("fma.rn.bf16x2 %0, %1, %2, %3;" : "=r"(d) : "r"(a), "r"(b), "r"(c)); return d; }
__device__ __forceinline__ uint32_t bf2add(uint32_t a, uint32_t b) { uint32_t d; asm("add.rn.bf16x2 %0, %1, %2;" : "=r"(d) : "r"(a), "r"(b)); return d; }
__device__ __forceinline__ uint32_t bf2mul(uint32_t a, uint32_t b) { uint32_t d; asm("mul.rn.bf16x2 %0, %1, %2;" : "=r"(d) : "r"(a), "r"(b)); return d; }
__device__ __forceinline__ uint32_t h2fma(uint32_t a, uint32_t b, uint32_t c) { uint32_t d; asm("fma.rn.f16x2 %0, %1, %2, %3;" : "=r"(d) : "r"(a), "r"(b), "r"(c)); return d; }
__device__ __forceinline__ uint32_t h2fma_sat(uint32_t a, uint32_t b, uint32_t c) { uint32_t d; asm("fma.rn.sat.f16x2 %0, %1, %2, %3;" : "=r"(d) : "r"(a), "r"(b), "r"(c)); return d; }
__device__ __forceinline__ uint32_t h2sub(uint32_t a, uint32_t b) { uint32_t d; asm("sub.f16x2 %0, %1, %2;" : "=r"(d) : "r"(a), "r"(b)); return d; }
__device__ __forceinline__ uint32_t h2mul(uint32_t a, uint32_t b) { uint32_t d; asm("mul.f16x2 %0, %1, %2;" : "=r"(d) : "r"(a), "r"(b)); return d; }
__device__ __forceinline__ uint32_t h2max(uint32_t a, uint32_t b) { uint32_t d; asm("max.f16x2 %0, %1, %2;" : "=r"(d) : "r"(a), "r"(b)); return d; }
__device__ __forceinline__ uint32_t h2min(uint32_t a, uint32_t b) { uint32_t d; asm("min.f16x2 %0, %1, %2;" : "=r"(d) : "r"(a), "r"(b)); return d; }
__device__ __forceinline__ uint32_t h2ex2(uint32_t a) { uint32_t d; asm("ex2.approx.f16x2 %0, %1;" : "=r"(d) : "r"(a)); return d; }
__device__ __forceinline__ uint32_t prmt(uint32_t a, uint32_t b, uint32_t s) { uint32_t d; asm("prmt.b32 %0, %1, %2, %3;" : "=r"(d) : "r"(a), "r"(b), "r"(s)); return d; }
__device__ __forceinline__ float ex2f(float a) { float d; asm("ex2.approx.ftz.f32 %0, %1;" : "=f"(d) : "f"(a)); return d; }
__device__ __forceinline__ float sqrt_fast(float a) { float d; asm("sqrt.approx.f32 %0, %1;" : "=f"(d) : "f"(a)); return d; }
__device__ __forceinline__ float rcp_fast(float a) { float d; asm("rcp.approx.f32 %0, %1;" : "=f"(d) : "f"(a)); return d; }
__device__ __forceinline__ float h_lo(uint32_t a) { float d; asm("{.reg .b16 l, h; mov.b32 {l, h}, %1; cvt.f32.f16 %0, l;}" : "=f"(d) : "r"(a)); return d; }
__device__ __forceinline__ float h_hi(uint32_t a) { float d; asm("{.reg .b16 l, h; mov.b32 {l, h}, %1; cvt.f32.f16 %0, h;}" : "=f"(d) : "r"(a)); return d; }
__device__ __forceinline__ uint32_t bc_lo(uint32_t a) { uint32_t d; asm("{.reg .b16 l, h; mov.b32 {l, h}, %1; mov.b32 %0, {l, l};}" : "=r"(d) : "r"(a)); return d; }
__device__ __forceinline__ uint32_t bc_hi(uint32_t a) { uint32_t d; asm("{.reg .b16 l, h; mov.b32 {l, h}, %1; mov.b32 %0, {h, h};}" : "=r"(d) : "r"(a)); return d; }
__device__ __forceinline__ uint32_t ldg_here(const void* p) { uint32_t v; asm volatile("ld.global.nc.u32 %0, [%1];" : "=r"(v) : "l"(p) : "memory"); return v; }

__device__ __forceinline__ void wgmma_qk(uint32_t (&d)[64], const uint32_t (&a)[4], uint64_t bdesc) {
    asm volatile("wgmma.mma_async.sync.aligned.m64n256k16.f16.f16.f16 {"
        "%0, %1, %2, %3, %4, %5, %6, %7, %8, %9, %10, %11, %12, %13, %14, %15, "
        "%16, %17, %18, %19, %20, %21, %22, %23, %24, %25, %26, %27, %28, %29, %30, %31, "
        "%32, %33, %34, %35, %36, %37, %38, %39, %40, %41, %42, %43, %44, %45, %46, %47, "
        "%48, %49, %50, %51, %52, %53, %54, %55, %56, %57, %58, %59, %60, %61, %62, %63"
        "}, {%64, %65, %66, %67}, %68, 0, 1, 1, 0;\n"
        : "=r"(d[0]), "=r"(d[1]), "=r"(d[2]), "=r"(d[3]), "=r"(d[4]), "=r"(d[5]), "=r"(d[6]), "=r"(d[7]),
          "=r"(d[8]), "=r"(d[9]), "=r"(d[10]), "=r"(d[11]), "=r"(d[12]), "=r"(d[13]), "=r"(d[14]), "=r"(d[15]),
          "=r"(d[16]), "=r"(d[17]), "=r"(d[18]), "=r"(d[19]), "=r"(d[20]), "=r"(d[21]), "=r"(d[22]), "=r"(d[23]),
          "=r"(d[24]), "=r"(d[25]), "=r"(d[26]), "=r"(d[27]), "=r"(d[28]), "=r"(d[29]), "=r"(d[30]), "=r"(d[31]),
          "=r"(d[32]), "=r"(d[33]), "=r"(d[34]), "=r"(d[35]), "=r"(d[36]), "=r"(d[37]), "=r"(d[38]), "=r"(d[39]),
          "=r"(d[40]), "=r"(d[41]), "=r"(d[42]), "=r"(d[43]), "=r"(d[44]), "=r"(d[45]), "=r"(d[46]), "=r"(d[47]),
          "=r"(d[48]), "=r"(d[49]), "=r"(d[50]), "=r"(d[51]), "=r"(d[52]), "=r"(d[53]), "=r"(d[54]), "=r"(d[55]),
          "=r"(d[56]), "=r"(d[57]), "=r"(d[58]), "=r"(d[59]), "=r"(d[60]), "=r"(d[61]), "=r"(d[62]), "=r"(d[63])
        : "r"(a[0]), "r"(a[1]), "r"(a[2]), "r"(a[3]), "l"(bdesc));
}
__device__ __forceinline__ void wgmma_pv0(uint32_t (&d)[6], uint32_t a0, uint32_t a1, uint32_t a2, uint32_t a3, uint64_t bdesc) {
    asm volatile("wgmma.mma_async.sync.aligned.m64n24k16.f16.f16.f16 {%0, %1, %2, %3, %4, %5}, {%6, %7, %8, %9}, %10, 0, 1, 1, 1;\n"
        : "=r"(d[0]), "=r"(d[1]), "=r"(d[2]), "=r"(d[3]), "=r"(d[4]), "=r"(d[5])
        : "r"(a0), "r"(a1), "r"(a2), "r"(a3), "l"(bdesc));
}
__device__ __forceinline__ void wgmma_pv(uint32_t (&d)[6], uint32_t a0, uint32_t a1, uint32_t a2, uint32_t a3, uint64_t bdesc) {
    asm volatile("wgmma.mma_async.sync.aligned.m64n24k16.f16.f16.f16 {%0, %1, %2, %3, %4, %5}, {%6, %7, %8, %9}, %10, 1, 1, 1, 1;\n"
        : "+r"(d[0]), "+r"(d[1]), "+r"(d[2]), "+r"(d[3]), "+r"(d[4]), "+r"(d[5])
        : "r"(a0), "r"(a1), "r"(a2), "r"(a3), "l"(bdesc));
}
__device__ __forceinline__ void wgmma_ss(float (&d)[16], uint64_t adesc, uint64_t bdesc) {
    asm volatile("wgmma.mma_async.sync.aligned.m64n32k16.f32.bf16.bf16 {"
        "%0, %1, %2, %3, %4, %5, %6, %7, %8, %9, %10, %11, %12, %13, %14, %15"
        "}, %16, %17, 1, 1, 1, 0, 1;\n"
        : "+f"(d[0]), "+f"(d[1]), "+f"(d[2]), "+f"(d[3]), "+f"(d[4]), "+f"(d[5]), "+f"(d[6]), "+f"(d[7]),
          "+f"(d[8]), "+f"(d[9]), "+f"(d[10]), "+f"(d[11]), "+f"(d[12]), "+f"(d[13]), "+f"(d[14]), "+f"(d[15])
        : "l"(adesc), "l"(bdesc));
}
__device__ __forceinline__ void wgmma_ss(float (&d)[32], uint64_t adesc, uint64_t bdesc) {
    asm volatile("wgmma.mma_async.sync.aligned.m64n64k16.f32.bf16.bf16 {"
        "%0, %1, %2, %3, %4, %5, %6, %7, %8, %9, %10, %11, %12, %13, %14, %15, "
        "%16, %17, %18, %19, %20, %21, %22, %23, %24, %25, %26, %27, %28, %29, %30, %31"
        "}, %32, %33, 1, 1, 1, 0, 1;\n"
        : "+f"(d[0]), "+f"(d[1]), "+f"(d[2]), "+f"(d[3]), "+f"(d[4]), "+f"(d[5]), "+f"(d[6]), "+f"(d[7]),
          "+f"(d[8]), "+f"(d[9]), "+f"(d[10]), "+f"(d[11]), "+f"(d[12]), "+f"(d[13]), "+f"(d[14]), "+f"(d[15]),
          "+f"(d[16]), "+f"(d[17]), "+f"(d[18]), "+f"(d[19]), "+f"(d[20]), "+f"(d[21]), "+f"(d[22]), "+f"(d[23]),
          "+f"(d[24]), "+f"(d[25]), "+f"(d[26]), "+f"(d[27]), "+f"(d[28]), "+f"(d[29]), "+f"(d[30]), "+f"(d[31])
        : "l"(adesc), "l"(bdesc));
}
__device__ __forceinline__ void wgmma_ss(float (&d)[64], uint64_t adesc, uint64_t bdesc) {
    asm volatile("wgmma.mma_async.sync.aligned.m64n128k16.f32.bf16.bf16 {"
        "%0, %1, %2, %3, %4, %5, %6, %7, %8, %9, %10, %11, %12, %13, %14, %15, "
        "%16, %17, %18, %19, %20, %21, %22, %23, %24, %25, %26, %27, %28, %29, %30, %31, "
        "%32, %33, %34, %35, %36, %37, %38, %39, %40, %41, %42, %43, %44, %45, %46, %47, "
        "%48, %49, %50, %51, %52, %53, %54, %55, %56, %57, %58, %59, %60, %61, %62, %63"
        "}, %64, %65, 1, 1, 1, 0, 1;\n"
        : "+f"(d[0]), "+f"(d[1]), "+f"(d[2]), "+f"(d[3]), "+f"(d[4]), "+f"(d[5]), "+f"(d[6]), "+f"(d[7]),
          "+f"(d[8]), "+f"(d[9]), "+f"(d[10]), "+f"(d[11]), "+f"(d[12]), "+f"(d[13]), "+f"(d[14]), "+f"(d[15]),
          "+f"(d[16]), "+f"(d[17]), "+f"(d[18]), "+f"(d[19]), "+f"(d[20]), "+f"(d[21]), "+f"(d[22]), "+f"(d[23]),
          "+f"(d[24]), "+f"(d[25]), "+f"(d[26]), "+f"(d[27]), "+f"(d[28]), "+f"(d[29]), "+f"(d[30]), "+f"(d[31]),
          "+f"(d[32]), "+f"(d[33]), "+f"(d[34]), "+f"(d[35]), "+f"(d[36]), "+f"(d[37]), "+f"(d[38]), "+f"(d[39]),
          "+f"(d[40]), "+f"(d[41]), "+f"(d[42]), "+f"(d[43]), "+f"(d[44]), "+f"(d[45]), "+f"(d[46]), "+f"(d[47]),
          "+f"(d[48]), "+f"(d[49]), "+f"(d[50]), "+f"(d[51]), "+f"(d[52]), "+f"(d[53]), "+f"(d[54]), "+f"(d[55]),
          "+f"(d[56]), "+f"(d[57]), "+f"(d[58]), "+f"(d[59]), "+f"(d[60]), "+f"(d[61]), "+f"(d[62]), "+f"(d[63])
        : "l"(adesc), "l"(bdesc));
}
__device__ __forceinline__ void wgmma_ss(float (&d)[96], uint64_t adesc, uint64_t bdesc) {
    asm volatile("wgmma.mma_async.sync.aligned.m64n192k16.f32.bf16.bf16 {"
        "%0, %1, %2, %3, %4, %5, %6, %7, %8, %9, %10, %11, %12, %13, %14, %15, "
        "%16, %17, %18, %19, %20, %21, %22, %23, %24, %25, %26, %27, %28, %29, %30, %31, "
        "%32, %33, %34, %35, %36, %37, %38, %39, %40, %41, %42, %43, %44, %45, %46, %47, "
        "%48, %49, %50, %51, %52, %53, %54, %55, %56, %57, %58, %59, %60, %61, %62, %63, "
        "%64, %65, %66, %67, %68, %69, %70, %71, %72, %73, %74, %75, %76, %77, %78, %79, "
        "%80, %81, %82, %83, %84, %85, %86, %87, %88, %89, %90, %91, %92, %93, %94, %95"
        "}, %96, %97, 1, 1, 1, 0, 1;\n"
        : "+f"(d[0]), "+f"(d[1]), "+f"(d[2]), "+f"(d[3]), "+f"(d[4]), "+f"(d[5]), "+f"(d[6]), "+f"(d[7]),
          "+f"(d[8]), "+f"(d[9]), "+f"(d[10]), "+f"(d[11]), "+f"(d[12]), "+f"(d[13]), "+f"(d[14]), "+f"(d[15]),
          "+f"(d[16]), "+f"(d[17]), "+f"(d[18]), "+f"(d[19]), "+f"(d[20]), "+f"(d[21]), "+f"(d[22]), "+f"(d[23]),
          "+f"(d[24]), "+f"(d[25]), "+f"(d[26]), "+f"(d[27]), "+f"(d[28]), "+f"(d[29]), "+f"(d[30]), "+f"(d[31]),
          "+f"(d[32]), "+f"(d[33]), "+f"(d[34]), "+f"(d[35]), "+f"(d[36]), "+f"(d[37]), "+f"(d[38]), "+f"(d[39]),
          "+f"(d[40]), "+f"(d[41]), "+f"(d[42]), "+f"(d[43]), "+f"(d[44]), "+f"(d[45]), "+f"(d[46]), "+f"(d[47]),
          "+f"(d[48]), "+f"(d[49]), "+f"(d[50]), "+f"(d[51]), "+f"(d[52]), "+f"(d[53]), "+f"(d[54]), "+f"(d[55]),
          "+f"(d[56]), "+f"(d[57]), "+f"(d[58]), "+f"(d[59]), "+f"(d[60]), "+f"(d[61]), "+f"(d[62]), "+f"(d[63]),
          "+f"(d[64]), "+f"(d[65]), "+f"(d[66]), "+f"(d[67]), "+f"(d[68]), "+f"(d[69]), "+f"(d[70]), "+f"(d[71]),
          "+f"(d[72]), "+f"(d[73]), "+f"(d[74]), "+f"(d[75]), "+f"(d[76]), "+f"(d[77]), "+f"(d[78]), "+f"(d[79]),
          "+f"(d[80]), "+f"(d[81]), "+f"(d[82]), "+f"(d[83]), "+f"(d[84]), "+f"(d[85]), "+f"(d[86]), "+f"(d[87]),
          "+f"(d[88]), "+f"(d[89]), "+f"(d[90]), "+f"(d[91]), "+f"(d[92]), "+f"(d[93]), "+f"(d[94]), "+f"(d[95])
        : "l"(adesc), "l"(bdesc));
}

#define H2C(x) ((uint32_t)(x) * 0x00010001u)
constexpr uint32_t C_2M15 = H2C(0x0200), C_N2M15 = H2C(0x8200), C_2P15 = H2C(0x7800), C_N2P15 = H2C(0xF800);
constexpr uint32_t C_512 = H2C(0x6000), C_N512 = H2C(0xE000), C_N13P5 = H2C(0xCAC0);
constexpr uint32_t PC0 = H2C(0x05a8), PC1 = H2C(0x27d9), PC2 = H2C(0x4581), PC3 = H2C(0x60ea);
constexpr float Q_SCALE = 0.25f * 1.4426950408889634f;

__device__ __forceinline__ uint32_t exp_mufu(uint32_t s, uint32_t cx) { return h2ex2(h2fma(s, C_512, cx)); }
__device__ __forceinline__ uint32_t exp_fma(uint32_t s, uint32_t cr, uint32_t ct, uint32_t z) {
    const uint32_t r = h2fma_sat(s, C_2M15, cr);
    const uint32_t t = h2fma(r, C_2P15, ct);
    const uint32_t f = h2sub(s, t);
    uint32_t p = h2fma(f, PC3, PC2);
    p = h2fma(p, f, PC1);
    p = h2fma_sat(p, f, PC0);
    uint32_t e;
    asm("shf.l.wrap.b32 %0, %1, %2, 10;" : "=r"(e) : "r"(z), "r"(r));
    return e + p;
}
__host__ __device__ constexpr bool is_poly(int i) { return (POLY_MASK >> (i & 31)) & 1; }

constexpr long long K_INC = 512;
constexpr long long V_INC = 32 - (32 << 16);

__device__ __forceinline__ void attn_fold(float (&O)[10], const uint32_t (&T)[6], float a0, float a1) {
    O[9] = fmaf(O[9], a1, h_lo(T[5]));
    O[8] = fmaf(O[8], a0, h_lo(T[4]));
#pragma unroll
    for (int i = 0; i < 4; i++) {
        O[2 * i] = fmaf(O[2 * i], (i & 1) ? a1 : a0, h_lo(T[i]));
        O[2 * i + 1] = fmaf(O[2 * i + 1], (i & 1) ? a1 : a0, h_hi(T[i]));
    }
}
__device__ __forceinline__ void attn_tile(float (&O)[10], const uint32_t (&q)[4], uint32_t& mrun, uint32_t& cxp, uint64_t kd, uint64_t vd, uint32_t coff, uint32_t z) {
    uint32_t S[64];
    wg_fence();
    wgmma_qk(S, q, kd);
    wg_commit();
    wg_wait<0>();
    pin(S);
    uint32_t ma = h2max(h2max(S[0], S[2]), S[4]), mb = h2max(h2max(S[1], S[3]), S[5]), mc = h2max(h2max(S[6], S[8]), S[10]), md = h2max(h2max(S[7], S[9]), S[11]);
#pragma unroll
    for (int i = 12; i < 60; i += 8) {
        ma = h2max(h2max(ma, S[i]), S[i + 2]);
        mb = h2max(h2max(mb, S[i + 1]), S[i + 3]);
        mc = h2max(h2max(mc, S[i + 4]), S[i + 6]);
        md = h2max(h2max(md, S[i + 5]), S[i + 7]);
    }
    ma = h2max(h2max(ma, S[60]), S[62]);
    mb = h2max(h2max(mb, S[61]), S[63]);
    ma = h2max(ma, mc);
    mb = h2max(mb, md);
    uint32_t m = h2max(prmt(ma, mb, 0x5410), prmt(ma, mb, 0x7632));
    m = h2max(m, __shfl_xor_sync(0xffffffffu, m, 1));
    m = h2max(h2max(m, mrun), __shfl_xor_sync(0xffffffffu, m, 2));
    mrun = m;
    const uint32_t cr = h2fma(m, C_N2M15, coff);
    const uint32_t ct = h2mul(cr, C_N2P15);
    const uint32_t cx = h2fma(ct, C_N512, C_N13P5);
    const uint32_t dd = h2sub(cx, cxp);
    cxp = cx;
    const float a0 = ex2f(h_lo(dd)), a1 = ex2f(h_hi(dd));
    uint32_t T[6];
    const uint32_t crA = bc_lo(cr), crB = bc_hi(cr), ctA = bc_lo(ct), ctB = bc_hi(ct), cxA = bc_lo(cx), cxB = bc_hi(cx);
    static_for<16>([&](auto kc) {
        constexpr int K = decltype(kc)::value;
#pragma unroll
        for (int j = 0; j < 4; j++) {
            const int i = 4 * K + ((ORDER >> (4 * j)) & 3);
            if (is_poly(i)) S[i] = exp_fma(S[i], (i & 1) ? crB : crA, (i & 1) ? ctB : ctA, z);
            else            S[i] = exp_mufu(S[i], (i & 1) ? cxB : cxA);
        }
        wg_fence();
        if (K == 0) wgmma_pv0(T, S[0], S[1], S[2], S[3], vd);
        else wgmma_pv(T, S[4 * K], S[4 * K + 1], S[4 * K + 2], S[4 * K + 3], vd + (uint64_t)(K * V_INC));
    });
    wg_commit();
    wg_wait<0>();
    pin(T);
    attn_fold(O, T, a0, a1);
}

__device__ __forceinline__ void attn_slow(const uint32_t (&qb)[4], uint8_t* ounit, int r0, int chunk0, int lane) {
    const int row = lane >> 1, half = lane & 1;
    float qf[16];
#pragma unroll
    for (int d = 0; d < 16; d += 2) {
        const int src = 4 * (row & 7) + ((d & 7) >> 1);
        const uint32_t v0 = __shfl_sync(0xffffffffu, qb[(d >> 3) * 2], src), v1 = __shfl_sync(0xffffffffu, qb[(d >> 3) * 2 + 1], src);
        const uint32_t w = (row & 8) ? v1 : v0;
        qf[d] = bf_lo(w) * Q_SCALE;
        qf[d + 1] = bf_hi(w) * Q_SCALE;
    }
    float m = -INFINITY, l = 0.f, o[16];
#pragma unroll
    for (int d = 0; d < 16; d++) o[d] = 0.f;
#pragma unroll 1
    for (int j = half * 1024; j < half * 1024 + 1024; j++) {
        uint32_t kv[16];
#pragma unroll
        for (int i = 0; i < 4; i++) {
            const uint4 t = __ldcg(&g_kvb[j * 4 + i]);
            kv[4 * i] = t.x; kv[4 * i + 1] = t.y; kv[4 * i + 2] = t.z; kv[4 * i + 3] = t.w;
        }
        float s = 0.f;
#pragma unroll
        for (int i = 0; i < 8; i++) {
            const uint32_t w = kv[4 * (i & 3) + (i >> 2)];
            s = fmaf(qf[2 * i + 1], bf_hi(w), fmaf(qf[2 * i], bf_lo(w), s));
        }
        const float mn = fmaxf(m, s), a = exp2f(m - mn), p = exp2f(s - mn);
        m = mn;
        l = fmaf(l, a, p);
#pragma unroll
        for (int i = 0; i < 8; i++) {
            const uint32_t w = kv[4 * (i & 3) + 2 + (i >> 2)];
            o[2 * i] = fmaf(o[2 * i], a, p * bf_lo(w));
            o[2 * i + 1] = fmaf(o[2 * i + 1], a, p * bf_hi(w));
        }
    }
    const float m2 = __shfl_xor_sync(0xffffffffu, m, 1), mn = fmaxf(m, m2), a = exp2f(m - mn);
    l *= a;
    l += __shfl_xor_sync(0xffffffffu, l, 1);
    const float inv = 1.f / l;
    uint32_t w[8];
#pragma unroll
    for (int i = 0; i < 8; i++) {
        float e0 = o[2 * i] * a, e1 = o[2 * i + 1] * a;
        e0 += __shfl_xor_sync(0xffffffffu, e0, 1);
        e1 += __shfl_xor_sync(0xffffffffu, e1, 1);
        w[i] = pack_bf16(e0 * inv, e1 * inv);
    }
    const int R = r0 + row;
    const uint4 val = half ? make_uint4(w[4], w[5], w[6], w[7]) : make_uint4(w[0], w[1], w[2], w[3]);
    *(uint4*)(ounit + R * 64 + (((chunk0 + half) ^ ((R >> 1) & 3)) << 4)) = val;
}

template <bool A128, int NR>
__device__ __forceinline__ void gemm_item(float (&c)[NR], uint32_t a) {
    const uint64_t ad = A128 ? mkdesc(a, 16, 1024, 1) : mkdesc(a, 16, 512, 2), bd = mkdesc(a + 8192, 8192, 1024, 1);
    wg_fence();
#pragma unroll
    for (int k = 0; k < 4; k++) wgmma_ss(c, ad + (A128 ? 2 * k : (k >> 1) * 256 + (k & 1) * 2), bd + k * 128);
    wg_commit();
}
template <int NU>
__device__ __forceinline__ void stage_h(const float (&c)[NU * 16], uint32_t dst, int row0, int lane) {
    const int row = row0 + ((lane >> 3) & 1) * 8 + (lane & 7), sw = (row >> 1) & 3;
#pragma unroll
    for (int j = 0; j < NU * 4; j += 2)
        stsm4(dst + (j >> 2) * UNIT + row * 64 + ((((j & 3) + (lane >> 4)) ^ sw) << 4),
              pack_bf16_relu(c[4 * j], c[4 * j + 1]), pack_bf16_relu(c[4 * j + 2], c[4 * j + 3]),
              pack_bf16_relu(c[4 * j + 4], c[4 * j + 5]), pack_bf16_relu(c[4 * j + 6], c[4 * j + 7]));
}

struct Params {
    const __nv_bfloat16* x;
    const uint8_t *wkp, *wvp, *w1p, *w2p, *wop;
    CUtensorMap wq, w1, w2, wo, out;
};

__global__ void __launch_bounds__(512, 1) fused_mqa_ffn_kernel(const __grid_constant__ Params P) {
    extern __shared__ __align__(1024) uint8_t smem[];
    const uint32_t sb = (uint32_t)__cvta_generic_to_shared(smem);
    const int tid = threadIdx.x, lane = tid & 31, g = lane >> 2, t4 = lane & 3;
    const int warp = __shfl_sync(0xffffffffu, tid >> 5, 0), wg = warp >> 2, wq4 = warp & 3;
    const int rb = blockIdx.x >> 2, c = blockIdx.x & 3;
    const uint32_t bars = sb + OFF_BAR;

    const int rg = warp >> 1;
    const uint32_t xb = sb + OFF_XN + rg * 8192, xbar = bars + BAR_X + 8 * rg;
    uint32_t epoch = 0;
    if (elect()) {
        if (!(warp & 1)) {
            mbar_init(xbar, 1);
            asm volatile("fence.mbarrier_init.release.cluster;" ::: "memory");
            mbar_expect(xbar, 8192);
            bulk_g2s(xb, (const uint8_t*)P.x + (size_t)rb * 65536 + rg * 8192, 8192, xbar);
        } else if (warp == 1) {
            prefetch_map(&P.wq);
        } else if (warp == 3) {
            mbar_init(bars + BAR_WKV, 1);
            asm volatile("fence.mbarrier_init.release.cluster;" ::: "memory");
            mbar_expect(bars + BAR_WKV, 32768);
            bulk_g2s(sb + OFF_WK, P.wkp, 16384, bars + BAR_WKV);
            bulk_g2s(sb + OFF_WV, P.wvp, 16384, bars + BAR_WKV);
        } else if (warp == 5) {
#pragma unroll
            for (int i = 0; i < 8; i++) mbar_init(bars + BAR_KV + 8 * i, 1);
#pragma unroll
            for (int i = 0; i < 2; i++) { mbar_init(bars + BAR_WQ + 8 * i, 1); mbar_init(bars + BAR_OH + 8 * i, 12); }
        } else if (warp == 7) {
#pragma unroll
            for (int i = 0; i < 16; i++) mbar_init(bars + BAR_R1 + 8 * i, 1);
        } else if (warp == 9) {
            prefetch_map(&P.w1);
        }
        asm volatile("fence.mbarrier_init.release.cluster;" ::: "memory");
    }
    if (wg == 3) {
        asm volatile("ld.relaxed.gpu.global.u32 %0, [%1];" : "=r"(epoch) : "l"(&g_sync[SY_EPOCH]) : "memory");
        *(uint32_t*)(smem + OFF_ONES + 4 * (tid - 384)) = 0x20002000u;
    }
    bar_sync(7, 512);
    auto issue_wq = [&](int i) {
        mbar_expect(bars + BAR_WQ + 8 * i, 65536);
        tma2(sb + OFF_WQ + i * 32768, &P.wq, bars + BAR_WQ + 8 * i, 128 * c, 256 * i);
        tma2(sb + OFF_WQ + 65536 + i * 32768, &P.wq, bars + BAR_WQ + 8 * i, 128 * c + 64, 256 * i);
    };
    __syncwarp();
    {
        uint4 xv[8];
        const int row = (lane >> 3) + 4 * (warp & 1);
        mbar_wait(xbar, 0);
        if (warp == 1 && elect()) { issue_wq(0); issue_wq(1); }
        __syncwarp();
#pragma unroll
        for (int i = 0; i < 8; i++)
            asm volatile("ld.shared.v4.b32 {%0, %1, %2, %3}, [%4];" : "=r"(xv[i].x), "=r"(xv[i].y), "=r"(xv[i].z), "=r"(xv[i].w)
                         : "r"(xb + row * 1024 + i * 128 + (lane & 7) * 16) : "memory");
        float acc[4][4];
#pragma unroll
        for (int i = 0; i < 4; i++)
#pragma unroll
            for (int j = 0; j < 4; j++) acc[i][j] = 0.f;
#pragma unroll
        for (int i = 0; i < 16; i++) {
            const uint32_t w0 = (i & 1) ? xv[i >> 1].z : xv[i >> 1].x, w1 = (i & 1) ? xv[i >> 1].w : xv[i >> 1].y;
            asm volatile("mma.sync.aligned.m16n8k16.row.col.f32.bf16.bf16.f32 {%0, %1, %2, %3}, {%4, %6, %5, %6}, {%4, %5}, {%0, %1, %2, %3};"
                         : "+f"(acc[i & 3][0]), "+f"(acc[i & 3][1]), "+f"(acc[i & 3][2]), "+f"(acc[i & 3][3])
                         : "r"(w0), "r"(w1), "r"(0x3f803f80u));
        }
        bar_sync(rg == 0 ? 0 : (rg < 4 ? rg + 1 : rg + 7), 64);
        float ssq = (g & 1) ? (acc[0][1] + acc[1][1]) + (acc[2][1] + acc[3][1]) : (acc[0][0] + acc[1][0]) + (acc[2][0] + acc[3][0]);
        float sum = (g & 1) ? (acc[0][3] + acc[1][3]) + (acc[2][3] + acc[3][3]) : (acc[0][2] + acc[1][2]) + (acc[2][2] + acc[3][2]);
        ssq = __shfl_sync(0xffffffffu, ssq, 4 * g + (g >> 1));
        sum = __shfl_sync(0xffffffffu, sum, 4 * g + (g >> 1));
        ssq += __shfl_xor_sync(0xffffffffu, ssq, 4);
        sum += __shfl_xor_sync(0xffffffffu, sum, 4);
        const float mean = sum * (1.f / DM);
        const float var = fmaxf(fmaf(-mean, mean, ssq * (1.f / DM)), 0.f);
        const float sd = bf_round(sqrt_fast(bf_round(bf_round(var) + 1e-5f)));
        const float r = rcp_fast(sd), rh = bf_round(r);
        const uint32_t rhi = pack_bf16(rh, rh), rlo = pack_bf16(r - rh, r - rh), nm = pack_bf16(-mean, -mean);
        auto norm2 = [&](uint32_t x) { const uint32_t d = bf2add(x, nm); return bf2fma(d, rhi, bf2mul(d, rlo)); };
        const uint32_t dst = xb + row * 128 + (((lane & 7) ^ row) << 4);
#pragma unroll
        for (int i = 0; i < 8; i++)
            asm volatile("st.shared.v4.b32 [%0], {%1, %2, %3, %4};" ::"r"(dst + i * 1024), "r"(norm2(xv[i].x)), "r"(norm2(xv[i].y)),
                         "r"(norm2(xv[i].z)), "r"(norm2(xv[i].w)) : "memory");
        mbar_wait(bars + BAR_WKV, 0);
        uint4* p = (uint4*)(smem + OFF_WK + ((tid >> 2) * 8 + 4 + (tid & 3)) * 32);
        const uint4 u = p[0], v = p[1];
        p[0] = v; p[1] = u;
    }
    fence_async_smem();
    bar_sync(6, 512);

    if (wg < 3) {
        uint32_t qb[4];
        uint4* gq = g_q + blockIdx.x * 1024 + (tid & 127);
        const uint32_t qx = sb + OFF_WK + (tid & 127) * 16;
        if (wg < 2) {
            bar_sync(9, 384);
            float a[32];
#pragma unroll
            for (int i = 0; i < 32; i++) a[i] = 0.f;
            pin(a);
            const uint64_t ad = mkdesc(sb + OFF_XN, 16, 8192, 1), bd = mkdesc(sb + OFF_WQ + wg * 65536, 16, 1024, 1);
            mbar_wait(bars + BAR_WQ, 0);
            wg_fence();
#pragma unroll
            for (int k = 0; k < 16; k++) wgmma_ss(a, ad + (k >> 2) * 64 + (k & 3) * 2, bd + k * 128);
            wg_commit();
            mbar_wait(bars + BAR_WQ + 8, 0);
            wg_fence();
#pragma unroll
            for (int k = 16; k < 32; k++) wgmma_ss(a, ad + (k >> 2) * 64 + (k & 3) * 2, bd + k * 128);
            wg_commit();
            wg_wait<0>();
            pin(a);
            bar_arrive(1, 512);
            uint32_t qa[16];
#pragma unroll
            for (int i = 0; i < 16; i++) qa[i] = pack_bf16(a[2 * i], a[2 * i + 1]);
            if (wg == 0) asm volatile("st.shared.v4.b32 [%0], {%1, %2, %3, %4};" ::"r"(qx), "r"(qa[4]), "r"(qa[5]), "r"(qa[6]), "r"(qa[7]) : "memory");
            bar_arrive(8, 384);
#pragma unroll
            for (int h = 1; h < 4; h++) gq[(4 * wg + h) * 128] = make_uint4(qa[4 * h], qa[4 * h + 1], qa[4 * h + 2], qa[4 * h + 3]);
#pragma unroll
            for (int i = 0; i < 4; i++) qb[i] = qa[i];
            int q2 = 0;
#pragma unroll
            for (int i = 0; i < 8; i++) {
                const int j = (i >> 1) * 4 + (i & 1);
                float s = bf_lo(qa[j]) * bf_lo(qa[j]);
                s = fmaf(bf_hi(qa[j]), bf_hi(qa[j]), s);
                s = fmaf(bf_lo(qa[j + 2]), bf_lo(qa[j + 2]), s);
                s = fmaf(bf_hi(qa[j + 2]), bf_hi(qa[j + 2]), s);
                s += __shfl_xor_sync(0xffffffffu, s, 1);
                s += __shfl_xor_sync(0xffffffffu, s, 2);
                q2 = max(q2, __float_as_int(s) & 0x7fffffff);
            }
            mbar_wait(bars + BAR_ST, 0);
            const int2 st = *(const int2*)(smem + OFF_BAR + STAT_VAL);
            const float qn2 = __int_as_float(q2) * (Q_SCALE * Q_SCALE), kn2 = __int_as_float(st.x), vx = __int_as_float(st.y);
            const bool ok = (qn2 * kn2 < 960.f * 960.f) && (qn2 < 1.6e7f) && (kn2 < 1.6e7f) && (vx < 1024.f) && (vx >= 0.015625f);
            const bool bad = bar_or(2 + wg, 128, !ok);
            if ((tid & 127) == 0) *(volatile int*)(smem + OFF_STAT + 4 * wg) = bad;
        } else {
            bar_sync(8, 384);
            asm volatile("ld.shared.v4.b32 {%0, %1, %2, %3}, [%4];" : "=r"(qb[0]), "=r"(qb[1]), "=r"(qb[2]), "=r"(qb[3]) : "r"(qx) : "memory");
            fence_async_smem();
            bar_arrive(1, 512);
        }
        bar_sync(11, 384);
        const int slowmask = __shfl_sync(0xffffffffu, *(volatile int*)(smem + OFF_STAT) + 2 * *(volatile int*)(smem + OFF_STAT + 4), 0);
        const uint32_t coff = H2C(27 - max((*(const int*)(smem + OFF_BAR + STAT_VAL + 4) >> 23) - 127, 0));
        const int nround = wg < 2 ? 3 : 4;
        const uint32_t heads = wg == 0 ? 0x0620 : wg == 1 ? 0x0754 : 0x7631;
        const uint64_t kd0 = mkdesc(sb + OFF_K, 16, 256, 3), vd0 = mkdesc(sb + OFF_V, OFF_ONES - OFF_V, 256, 3);
#pragma unroll 1
        for (int r = 0; r < nround; r++) {
            const bool last = r >= 2, helper = last && wg == 2;
            const int h = (heads >> (4 * r)) & 7, r0 = wq4 * 16;
            uint8_t* ounit = g_o + (size_t)((rb * 8 + h) * 2 + (c >> 1)) * UNIT;
            const bool slow = (slowmask >> (h >> 2)) & 1;
            uint4 qn = make_uint4(0, 0, 0, 0);
            if (!slow) {
                float O[10];
#pragma unroll
                for (int i = 0; i < 10; i++) O[i] = 0.f;
                uint32_t q[4];
#pragma unroll
                for (int i = 3; i >= 0; i--) q[i] = pack_f16(bf_lo(qb[i]) * (Q_SCALE / 32.f), bf_hi(qb[i]) * (Q_SCALE / 32.f));
                uint32_t mrun = H2C(0xFBFF), cxp = H2C(0x7C00);
                const bool kvwait = r == 0 || slowmask != 0;
                const int t0 = helper ? SPLIT_T : 0, t1 = (last && wg < 2) ? SPLIT_T : 8;
                uint64_t kd = kd0 + t0 * K_INC, vd = vd0 + (uint64_t)(t0 * 16 * V_INC);
#pragma unroll 1
                for (int t = t0; t < t1; t++) {
                    if (kvwait) mbar_wait(bars + BAR_KV + 8 * t, 0);
                    attn_tile(O, q, mrun, cxp, kd, vd, coff, tid);
                    kd += K_INC;
                    vd += (uint64_t)(16 * V_INC);
                }
                if (r + 1 < nround) qn = __ldcg(gq + ((heads >> (4 * r + 4)) & 7) * 128);
                if (last) {
                    float* mb = (float*)(smem + OFF_MERGE + (h & 1) * 5632) + (tid & 127);
                    if (helper) {
                        if (r == 2) bar_sync(13, 256);
#pragma unroll
                        for (int i = 0; i < 10; i++) mb[128 * i] = O[i];
                        mb[128 * 10] = __uint_as_float(cxp);
                        bar_arrive(14 + (h & 1), 256);
                    } else {
                        bar_sync(14 + (h & 1), 256);
                        const uint32_t cxo = __float_as_uint(mb[128 * 10]);
                        const uint32_t cxm = h2min(cxp, cxo), da = h2sub(cxm, cxp), db = h2sub(cxm, cxo);
                        const float e0 = ex2f(h_lo(da)), e1 = ex2f(h_hi(da)), b0 = ex2f(h_lo(db)), b1 = ex2f(h_hi(db));
#pragma unroll
                        for (int i = 0; i < 10; i++) {
                            const bool hi = i < 8 ? (i & 2) : (i & 1);
                            O[i] = fmaf(O[i], hi ? e1 : e0, mb[128 * i] * (hi ? b1 : b0));
                        }
                    }
                }
                if (!helper) {
                    const float i0 = 2.f * rcp_fast(O[8]), i1 = 2.f * rcp_fast(O[9]);
                    const int R = r0 + g;
                    uint8_t* p = ounit + R * 64 + ((((c & 1) * 2 + (t4 >> 1)) ^ ((R >> 1) & 3)) << 4) + (t4 & 1) * 8;
                    *(uint2*)p = make_uint2(pack_bf16(O[0] * i0, O[1] * i0), pack_bf16(O[4] * i0, O[5] * i0));
                    *(uint2*)(p + 512) = make_uint2(pack_bf16(O[2] * i1, O[3] * i1), pack_bf16(O[6] * i1, O[7] * i1));
                }
            } else {
                if (r + 1 < nround) qn = __ldcg(gq + ((heads >> (4 * r + 4)) & 7) * 128);
                if (!helper) attn_slow(qb, ounit, r0, (c & 1) * 2, lane);
            }
            __syncwarp();
            if (lane == 0 && !helper) {
                if (last) signal_add(&g_sync[SY_O + (rb * 3 + 2) * 32]);
                else asm volatile("mbarrier.arrive.shared::cta.b64 _, [%0];" ::"r"(bars + BAR_OH + 8 * r) : "memory");
            }
            qb[0] = qn.x; qb[1] = qn.y; qb[2] = qn.z; qb[3] = qn.w;
        }
    } else {
        const bool prod = warp == 12;
        const bool kvwarp = wq4 == c;
        {
            float a[16];
#pragma unroll
            for (int i = 0; i < 16; i++) a[i] = 0.f;
            pin(a);
            const uint64_t ad = mkdesc(sb + OFF_XN, 16, 8192, 1), bd = mkdesc(sb + OFF_WK, 16384, 256, 3);
            wg_fence();
#pragma unroll
            for (int k = 0; k < 32; k++) wgmma_ss(a, ad + (k >> 2) * 64 + (k & 3) * 2, bd + k * 32);
            wg_commit();
            if (lane < 4) {
                const int j = wq4 * 4 + lane, q = 2 * c + (j >> 3), kc = j & 7;
                bulk_s2g(g_xn + (size_t)(rb * 8 + kc) * 8192 + q * 1024, sb + OFF_XN + q * 8192 + kc * 1024, 1024);
                bulk_commit();
            }
            __syncwarp();
            wg_wait<0>();
            pin(a);
            bar_arrive(9, 384);
            if (kvwarp) {
                uint32_t w[8];
#pragma unroll
                for (int i = 0; i < 8; i++) w[i] = pack_bf16(a[2 * i], a[2 * i + 1]);
                uint8_t* stg = smem + OFF_STAT;
                const int key0 = rb * 64 + c * 16;
#pragma unroll
                for (int hh = 0; hh < 2; hh++) {
                    const int kr = g + 8 * hh, sw = (kr >> 2) & 1;
#pragma unroll
                    for (int b = 0; b < 2; b++) {
                        const uint32_t kk = w[2 * b + hh], vv = w[4 + 2 * b + hh];
                        *(uint32_t*)(stg + kr * 32 + ((b ^ sw) << 4) + 4 * t4) = pack_f16(bf_lo(kk) * 0.0625f, bf_hi(kk) * 0.0625f);
                        *(uint32_t*)(stg + 512 + kr * 32 + (((t4 & 1) ^ sw) << 4) + 8 * b + 4 * (t4 >> 1)) = pack_f16(bf_lo(vv) * 0.00390625f, bf_hi(vv) * 0.00390625f);
                    }
                }
                fence_async_smem();
                __syncwarp();
                if (elect()) {
                    bulk_s2g(g_kv + key0 * 32, sb + OFF_STAT, 512);
                    bulk_s2g(g_kv + 65536 + key0 * 32, sb + OFF_STAT + 512, 512);
                    bulk_commit();
                }
                __syncwarp();
                int k2 = 0, vm = 0;
#pragma unroll
                for (int hh = 0; hh < 2; hh++) {
                    g_kvb[(key0 + g + 8 * hh) * 4 + t4] = make_uint4(w[hh], w[2 + hh], w[4 + hh], w[6 + hh]);
                    float s = 0.f;
#pragma unroll
                    for (int b = 0; b < 2; b++) {
                        const uint32_t kk = w[2 * b + hh], vv = w[4 + 2 * b + hh];
                        s = fmaf(bf_lo(kk), bf_lo(kk), fmaf(bf_hi(kk), bf_hi(kk), s));
                        vm = max(vm, max((int)((vv << 16) & 0x7fffffff), (int)(vv & 0x7fff0000)));
                    }
                    s += __shfl_xor_sync(0xffffffffu, s, 1);
                    s += __shfl_xor_sync(0xffffffffu, s, 2);
                    k2 = max(k2, __float_as_int(s) & 0x7fffffff);
                }
                k2 = __reduce_max_sync(0xffffffffu, k2);
                vm = __reduce_max_sync(0xffffffffu, vm);
                if (lane < 2)
                    asm volatile("red.relaxed.gpu.global.max.u64 [%0], %1;" ::"l"(&g_sync[SY_MAX + 2 * lane]),
                                 "l"(((unsigned long long)(epoch + 1) << 32) | (uint32_t)(lane ? vm : k2)) : "memory");
            }
            bulk_wait_all();
            bar_sync(5, 128);
            if (kvwarp && lane == 0) signal_add(&g_sync[SY_KV]);
            __syncwarp();
        }
        if (prod) flag_wait(&g_sync[SY_KV], (epoch + 1) * 128);
        bar_sync(1, 512);
        const uint32_t ring = __shfl_sync(0xffffffffu, sb, 0) + OFF_RING;
        const uint32_t rbar = ring - OFF_RING + OFF_BAR;
        const uint8_t* xn_src = g_xn + (size_t)rb * 65536;
        auto issue1 = [&](int it) {
            const int pass = it / 9, kc = it - 9 * pass, col = 448 * c + (pass ? 64 + 128 * pass : 0);
            const uint32_t slot = ring + (it % 3) * 32768, bar = rbar + BAR_R1 + (it % 3) * 8;
            mbar_expect(bar, pass ? 24576 : 32768);
            bulk_g2s(slot, xn_src + kc * 8192, 8192, bar);
            tma2(slot + 8192, &P.w1, bar, col, kc * 64);
            tma2(slot + 16384, &P.w1, bar, col + 64, kc * 64);
            if (!pass) tma2(slot + 24576, &P.w1, bar, col + 128, kc * 64);
        };
        if (prod && elect()) {
            unsigned long long mk, mv;
            asm volatile("ld.relaxed.gpu.global.v2.u64 {%0, %1}, [%2];" : "=l"(mk), "=l"(mv) : "l"(&g_sync[SY_MAX]) : "memory");
            fence_async_global();
#pragma unroll
            for (int t = 0; t < 8; t++) {
                const uint32_t bar = bars + BAR_KV + 8 * t;
                mbar_expect(bar, 16384);
                bulk_g2s(sb + OFF_K + t * 8192, g_kv + t * 8192, 8192, bar);
                bulk_g2s(sb + OFF_V + t * 8192, g_kv + 65536 + t * 8192, 8192, bar);
                if (t == 1) {
                    issue1(0);
                    *(uint2*)(smem + OFF_BAR + STAT_VAL) = make_uint2((uint32_t)mk, (uint32_t)mv);
                    asm volatile("mbarrier.arrive.shared::cta.b64 _, [%0];" ::"r"(bars + BAR_ST) : "memory");
                    issue1(1);
                    issue1(2);
                }
            }
            if (blockIdx.x == 0) asm volatile("st.relaxed.gpu.global.u32 [%0], %1;" ::"l"(&g_sync[SY_EPOCH]), "r"(epoch + 1) : "memory");
            l2_prefetch(P.w1p + blockIdx.x * 14336, 14336);
            prefetch_map(&P.w2); prefetch_map(&P.wo); prefetch_map(&P.out);
            l2_prefetch(P.w2p + blockIdx.x * 14336, 14336);
            l2_prefetch(P.wop + blockIdx.x * 4096, 4096);
        }
        __syncwarp();
        uint8_t* h_dst = g_h + (size_t)(rb * 56 + 14 * c) * UNIT;
        auto ffn1_pass = [&](auto nu, int pass) {
            constexpr int NU = decltype(nu)::value;
            float a[NU * 16];
#pragma unroll
            for (int i = 0; i < NU * 16; i++) a[i] = 0.f;
            pin(a);
#pragma unroll 1
            for (int j = 0; j < 8; j++) {
                const int it = 9 * pass + j, s = j % 3;
                mbar_wait(rbar + BAR_R1 + s * 8, (it / 3 - (s == 2 ? pass : 0)) & 1);
                gemm_item<true>(a, ring + s * 32768);
                wg_wait<1>();
                bar_sync(5, 128);
                if (prod && it > 0 && j != 6 && it != 25 && elect()) {
                    if (j == 0) bulk_wait_read();
                    issue1(it + 2);
                }
                __syncwarp();
            }
            wg_wait<0>();
            pin(a);
            stage_h<NU>(a, ring + 2 * 32768, wq4 * 16, lane);
            fence_async_smem();
            bar_sync(5, 128);
            if (prod && elect()) {
                if (pass < 2) issue1(9 * pass + 10);
                bulk_s2g(h_dst + (pass ? 2 + 4 * pass : 0) * UNIT, ring + 2 * 32768, NU * UNIT);
                bulk_commit();
                if (pass == 2) {
                    bulk_wait_all();
                    signal_add(&g_sync[SY_H + rb * 32]);
                }
            }
            __syncwarp();
        };
        ffn1_pass(std::integral_constant<int, 6>{}, 0);
#pragma unroll 1
        for (int pass = 1; pass < 3; pass++) ffn1_pass(std::integral_constant<int, 4>{}, pass);
        float a[64];
        {
            const __nv_bfloat16* xp = P.x + (size_t)(rb * 64 + wq4 * 16 + g) * DM + c * 128 + 2 * t4;
#pragma unroll
            for (int j = 0; j < 16; j++) {
                const uint32_t v0 = ldg_here(xp + 8 * j), v1 = ldg_here(xp + 8 * DM + 8 * j);
                a[4 * j] = bf_lo(v0); a[4 * j + 1] = bf_hi(v0); a[4 * j + 2] = bf_lo(v1); a[4 * j + 3] = bf_hi(v1);
            }
            pin(a);
        }
        const uint8_t* h_src = g_h + (size_t)rb * 56 * UNIT;
        const uint8_t* o_src = g_o + (size_t)rb * 16 * UNIT;
        auto issue2 = [&](int it, int parts) {
            const uint32_t slot = ring + (it < 28 ? it & 3 : (it - 28) % 3) * 24576;
            const uint32_t bar = it < 28 ? rbar + BAR_R2 + (it & 3) * 8 : rbar + BAR_O + (it - 28) * 8;
            const int h = (0x76352140u >> (4 * ((it - 28) & 7))) & 7;
            if (parts & 1) {
                mbar_expect(bar, 24576);
#pragma unroll
                for (int j = 0; j < 2; j++) {
                    if (it < 28) tma2(slot + 8192 + j * 8192, &P.w2, bar, 128 * c + 64 * j, it * 64);
                    else tma3(slot + 8192 + j * 8192, &P.wo, bar, 128 * c + 64 * j, 16 * h, 0);
                }
            }
            if (parts & 2) bulk_g2s(slot, it < 28 ? h_src + it * 8192 : o_src + h * 8192, 8192, bar);
        };
        if (prod) {
            if (elect()) {
#pragma unroll 1
                for (int i = 0; i < 4; i++) issue2(i, 1);
            }
            __syncwarp();
            flag_wait(&g_sync[SY_H + rb * 32], (epoch + 1) * 4);
            if (elect()) {
                fence_async_global();
#pragma unroll 1
                for (int i = 0; i < 4; i++) issue2(i, 2);
            }
            __syncwarp();
        }
        bar_sync(5, 128);
#pragma unroll 1
        for (int it = 0; it < 28; it++) {
            mbar_wait(rbar + BAR_R2 + (it & 3) * 8, (it >> 2) & 1);
            gemm_item<false>(a, ring + (it & 3) * 24576);
            wg_wait<1>();
            bar_sync(5, 128);
            if (prod && it >= 1 && it < 25 && elect()) issue2(it + 3, 3);
            __syncwarp();
        }
        wg_wait<0>();
        pin(a);
        bar_arrive(13, 256);
        bar_sync(5, 128);
#pragma unroll 1
        for (int seg = 0; seg < 3; seg++) {
            const int first = 28 + 3 * seg, n = seg < 2 ? 3 : 2;
            if (prod) {
                uint32_t* f = &g_sync[SY_O + (rb * 3 + seg) * 32];
                if (elect()) {
#pragma unroll 1
                    for (int i = first; i < first + n; i++) issue2(i, 1);
                }
                __syncwarp();
                if (seg < 2) {
                    mbar_wait(bars + BAR_OH + 8 * seg, 0);
                    if (elect()) signal_add(f);
                    __syncwarp();
                }
                flag_wait(f, (epoch + 1) * (seg == 2 ? 32 : 4));
                if (elect()) {
                    fence_async_global();
#pragma unroll 1
                    for (int i = first; i < first + n; i++) issue2(i, 2);
                }
                __syncwarp();
            }
            bar_sync(5, 128);
#pragma unroll 1
            for (int i = 0; i < n; i++) {
                mbar_wait(rbar + BAR_O + (3 * seg + i) * 8, 0);
                gemm_item<false>(a, ring + i * 24576);
            }
            wg_wait<0>();
            pin(a);
            if (seg < 2) bar_sync(5, 128);
        }
        {
            const uint32_t ob = ring + 49152;
            const int row = wq4 * 16 + ((lane >> 3) & 1) * 8 + (lane & 7);
#pragma unroll
            for (int j = 0; j < 16; j += 2)
                stsm4(ob + (j >> 3) * 8192 + row * 128 + ((((j & 7) + (lane >> 4)) ^ (row & 7)) << 4),
                      pack_bf16(a[4 * j], a[4 * j + 1]), pack_bf16(a[4 * j + 2], a[4 * j + 3]),
                      pack_bf16(a[4 * j + 4], a[4 * j + 5]), pack_bf16(a[4 * j + 6], a[4 * j + 7]));
            fence_async_smem();
            __syncwarp();
            if (elect()) {
                tma2_store(&P.out, ob + wq4 * 2048, c * 128, rb * 64 + wq4 * 16);
                tma2_store(&P.out, ob + 8192 + wq4 * 2048, c * 128 + 64, rb * 64 + wq4 * 16);
                bulk_commit();
                bulk_wait_read();
            }
        }
    }
}

typedef CUresult (*EncodeFn)(CUtensorMap*, CUtensorMapDataType, cuuint32_t, void*, const cuuint64_t*, const cuuint64_t*, const cuuint32_t*,
                             const cuuint32_t*, CUtensorMapInterleave, CUtensorMapSwizzle, CUtensorMapL2promotion, CUtensorMapFloatOOBfill);

void encode(EncodeFn fn, CUtensorMap* m, const void* p, int rank, const cuuint64_t* dims, const cuuint64_t* strides, const cuuint32_t* box, CUtensorMapSwizzle sw) {
    const cuuint32_t es[5] = {1, 1, 1, 1, 1};
    fn(m, CU_TENSOR_MAP_DATA_TYPE_BFLOAT16, rank, const_cast<void*>(p), dims, strides, box, es, CU_TENSOR_MAP_INTERLEAVE_NONE, sw,
       CU_TENSOR_MAP_L2_PROMOTION_L2_256B, CU_TENSOR_MAP_FLOAT_OOB_FILL_NONE);
}

}

extern "C" void kernel_launch(void* const* d_in, const int* in_sizes, int n_in, void* d_out, int out_size) {
    (void)in_sizes; (void)n_in; (void)out_size;
    static EncodeFn fn = nullptr;
    if (!fn) {
        void* p = nullptr;
        cudaDriverEntryPointQueryResult qr;
        cudaGetDriverEntryPoint("cuTensorMapEncodeTiled", &p, cudaEnableDefault, &qr);
        fn = (EncodeFn)p;
        cudaFuncSetAttribute(fused_mqa_ffn_kernel, cudaFuncAttributeMaxDynamicSharedMemorySize, SMEM_BYTES);
    }
    Params P;
    {
        const cuuint64_t d[2] = {DM, DM}, s[1] = {DM * 2};
        const cuuint32_t b[2] = {64, 256};
        encode(fn, &P.wq, d_in[1], 2, d, s, b, CU_TENSOR_MAP_SWIZZLE_128B);
    }
    {
        const cuuint64_t d[2] = {DFF, DM}, s[1] = {DFF * 2};
        const cuuint32_t b[2] = {64, 64};
        encode(fn, &P.w1, d_in[6], 2, d, s, b, CU_TENSOR_MAP_SWIZZLE_128B);
    }
    {
        const cuuint64_t d[2] = {DM, DFF}, s[1] = {DM * 2};
        const cuuint32_t b[2] = {64, 64};
        encode(fn, &P.w2, d_in[7], 2, d, s, b, CU_TENSOR_MAP_SWIZZLE_128B);
    }
    {
        const cuuint64_t d[3] = {DM, 128, 4}, s[2] = {DM * 2, 128 * DM * 2};
        const cuuint32_t b[3] = {64, 16, 4};
        encode(fn, &P.wo, d_in[4], 3, d, s, b, CU_TENSOR_MAP_SWIZZLE_128B);
    }
    {
        const cuuint64_t d[2] = {DM, SEQ}, s[1] = {DM * 2};
        const cuuint32_t b[2] = {64, 16};
        encode(fn, &P.out, d_out, 2, d, s, b, CU_TENSOR_MAP_SWIZZLE_128B);
    }
    P.x = (const __nv_bfloat16*)d_in[0];
    P.wkp = (const uint8_t*)d_in[2];
    P.wvp = (const uint8_t*)d_in[3];
    P.w1p = (const uint8_t*)d_in[6];
    P.w2p = (const uint8_t*)d_in[7];
    P.wop = (const uint8_t*)d_in[4];
    fused_mqa_ffn_kernel<<<128, 512, SMEM_BYTES, cudaStreamPerThread>>>(P);
}
```
